```python
import torch

def _softmax(x, axis=-1):
    return torch.softmax(x, dim=axis)
def _gelu(x):
    return torch.nn.functional.gelu(x, approximate="tanh")
def _silu(x):
    return torch.nn.functional.silu(x)
def _sigmoid(x):
    return torch.sigmoid(x)
def _layernorm(x, axis=-1, eps=1e-5):
    m = x.mean(dim=axis, keepdim=True)
    v = x.var(dim=axis, keepdim=True, unbiased=False)
    return (x - m) / torch.sqrt(v + eps)
def _scatter_add(tgt, idx, src, axis=0):
    return tgt.clone().index_add_(axis, idx, src)
def _segment_sum(src, seg, n):
    out = torch.zeros((n,) + src.shape[1:], dtype=src.dtype)
    return out.index_add_(0, seg, src)
def _pad(x, pw):
    flat = tuple(v for pair in reversed(pw) for v in pair)
    return torch.nn.functional.pad(x, flat)

kernel_name = 'sequential_preLN__spectral_gfnet__glu_gated_geglu__prompt'

def setup_inputs():

    _w = (lambda a: (lambda t: t.to(torch.bfloat16) if t.is_floating_point() else t)(torch.as_tensor(a)))
    def _A_setup():
        B, S, D = 1, 2048, 512
        Df = D // 2 + 1
        return {
            "x": _w((lambda *s: torch.randn(*s, dtype=torch.bfloat16) * 0.05)(B, S, D)),
            "w_r": _w((lambda *s: torch.randn(*s, dtype=torch.bfloat16) * 0.4)(S, Df) * 0.02),
            "w_i": _w((lambda *s: torch.randn(*s, dtype=torch.bfloat16) * 0.4)(S, Df) * 0.02),
        }
    _A_in = _A_setup()

    def _B_setup():
        B, S, Dm, Df = 1, 2048, 512, 1376
        return {
            "x": _w((lambda *s: torch.randn(*s, dtype=torch.bfloat16) * 0.05)(B, S, Dm)),
            "w_gate": _w((lambda *s: torch.randn(*s, dtype=torch.bfloat16) * 0.4)(Dm, Df) * (Dm ** -0.5)),
            "w_up": _w((lambda *s: torch.randn(*s, dtype=torch.bfloat16) * 0.4)(Dm, Df) * (Dm ** -0.5)),
            "w_down": _w((lambda *s: torch.randn(*s, dtype=torch.bfloat16) * 0.4)(Df, Dm) * (Df ** -0.5)),
        }
    _B_in = _B_setup()

    return {
        "A_x": _A_in["x"],
        "A_w_r": _A_in["w_r"],
        "A_w_i": _A_in["w_i"],
        "B_x": _B_in["x"],
        "B_w_gate": _B_in["w_gate"],
        "B_w_up": _B_in["w_up"],
        "B_w_down": _B_in["w_down"],
    }

def reference(A_x, A_w_r, A_w_i, B_x, B_w_gate, B_w_up, B_w_down):
    def _A_ref(x, w_r, w_i):
        B, S, D = x.shape
        X = (lambda x, axes=(-2,-1): torch.fft.rfft2(x.float(), dim=axes))(x, axes=(-2, -1))
        W = w_r + 1j * w_i
        X = X * W
        y = (lambda x, s, axes=(-2,-1): torch.fft.irfft2(x, s=s, dim=axes).to(torch.bfloat16))(X, (S, D), axes=(-2, -1))
        return y

    def _B_ref(x, w_gate, w_up, w_down):
        g = torch.einsum("bsd,df->bsf", x, w_gate)
        u = torch.einsum("bsd,df->bsf", x, w_up)
        h = _gelu(g) * u
        return torch.einsum("bsf,fd->bsd", h, w_down)

    x = A_x
    h = x + _A_ref(_layernorm(x, axis=-1), A_w_r, A_w_i)
    h2 = h + _B_ref(_layernorm(h, axis=-1), B_w_gate, B_w_up, B_w_down)
    return h2
```

```cpp
#include <cuda_runtime.h>
#include <cuda_bf16.h>
#include <cuda.h>
#include <stdint.h>

namespace {

__device__ const uint32_t g_tab[9600] __attribute__((aligned(128))) = {
  0x3f803f80,0x3f803f80,0x3f803f80,0x3f803f80,0x3f803f80,0xbf80bf80,0x3f803f80,0xbf80bf80,0x3f803f80,0x3f803f80,0x3f803f80,0x3f803f80,
  0x3f803f80,0xbf80bf80,0x3f803f80,0xbf80bf80,0x3f80,0x3f80,0xbf80,0xbf80,0xbec43f6d,0x3ec4bf6d,0x3ec4bf6d,0xbec43f6d,
  0xbf353f35,0xbf353f35,0x3f35bf35,0x3f35bf35,0xbf6d3ec4,0x3f6dbec4,0x3f6dbec4,0xbf6d3ec4,0xbf803f80,0xbf803f80,0xbf803f80,0xbf803f80,
  0xbf353f35,0x3f35bf35,0xbf353f35,0x3f35bf35,0,0,0,0,0x3f35bf35,0xbf353f35,0x3f35bf35,0xbf353f35,
  0x3f80,0x3f80,0xbf80,0xbf80,0x3f6d3ec4,0xbf6dbec4,0xbf6dbec4,0x3f6d3ec4,0x3f35bf35,0x3f35bf35,0xbf353f35,0xbf353f35,
  0xbec4bf6d,0x3ec43f6d,0x3ec43f6d,0xbec4bf6d,0x3f803f80,0x3f803f80,0x3f803f80,0x3f803f80,0,0,0,0,
  0xbf80bf80,0xbf80bf80,0xbf80bf80,0xbf80bf80,0,0,0,0,0x3f80,0x3f80,0xbf80,0xbf80,
  0xbf6dbec4,0x3f6d3ec4,0x3f6d3ec4,0xbf6dbec4,0x3f35bf35,0x3f35bf35,0xbf353f35,0xbf353f35,0x3ec43f6d,0xbec4bf6d,0xbec4bf6d,0x3ec43f6d,
  0xbf803f80,0xbf803f80,0xbf803f80,0xbf803f80,0x3f35bf35,0xbf353f35,0x3f35bf35,0xbf353f35,0,0,0,0,
  0xbf353f35,0x3f35bf35,0xbf353f35,0x3f35bf35,0x3f80,0x3f80,0xbf80,0xbf80,0x3ec4bf6d,0xbec43f6d,0xbec43f6d,0x3ec4bf6d,
  0xbf353f35,0xbf353f35,0x3f35bf35,0x3f35bf35,0x3f6dbec4,0xbf6d3ec4,0xbf6d3ec4,0x3f6dbec4,0x80008000,0x80008000,0x80008000,0x80008000,
  0x80008000,0x80008000,0x80008000,0x80008000,0x80008000,0x80008000,0x80008000,0x80008000,0x80008000,0x80008000,0x80008000,0x80008000,
  0xbf808000,0xbf808000,0x3f808000,0x3f808000,0xbf6dbec4,0x3f6d3ec4,0x3f6d3ec4,0xbf6dbec4,0xbf35bf35,0xbf35bf35,0x3f353f35,0x3f353f35,
  0xbec4bf6d,0x3ec43f6d,0x3ec43f6d,0xbec4bf6d,0x80008000,0x80008000,0x80008000,0x80008000,0x3f35bf35,0xbf353f35,0x3f35bf35,0xbf353f35,
  0x3f80bf80,0x3f80bf80,0x3f80bf80,0x3f80bf80,0x3f35bf35,0xbf353f35,0x3f35bf35,0xbf353f35,0x3f808000,0x3f808000,0xbf808000,0xbf808000,
  0x3ec4bf6d,0xbec43f6d,0xbec43f6d,0x3ec4bf6d,0xbf35bf35,0xbf35bf35,0x3f353f35,0x3f353f35,0xbf6d3ec4,0x3f6dbec4,0x3f6dbec4,0xbf6d3ec4,
  0x80008000,0x80008000,0x80008000,0x80008000,0xbf80bf80,0x3f803f80,0xbf80bf80,0x3f803f80,0x80008000,0x80008000,0x80008000,0x80008000,
  0x3f803f80,0xbf80bf80,0x3f803f80,0xbf80bf80,0xbf808000,0xbf808000,0x3f808000,0x3f808000,0x3ec4bf6d,0xbec43f6d,0xbec43f6d,0x3ec4bf6d,
  0x3f353f35,0x3f353f35,0xbf35bf35,0xbf35bf35,0xbf6d3ec4,0x3f6dbec4,0x3f6dbec4,0xbf6d3ec4,0x80008000,0x80008000,0x80008000,0x80008000,
  0x3f35bf35,0xbf353f35,0x3f35bf35,0xbf353f35,0xbf803f80,0xbf803f80,0xbf803f80,0xbf803f80,0x3f35bf35,0xbf353f35,0x3f35bf35,0xbf353f35,
  0x3f808000,0x3f808000,0xbf808000,0xbf808000,0xbf6dbec4,0x3f6d3ec4,0x3f6d3ec4,0xbf6dbec4,0x3f353f35,0x3f353f35,0xbf35bf35,0xbf35bf35,
  0xbec4bf6d,0x3ec43f6d,0x3ec43f6d,0xbec4bf6d,0,0,0,0,0,0,0,0,
  0,0,0,0,0,0,0,0,0x3f800000,0x3f800000,0xbf800000,0xbf800000,
  0x3f6d3ec4,0xbf6dbec4,0xbf6dbec4,0x3f6d3ec4,0x3f353f35,0x3f353f35,0xbf35bf35,0xbf35bf35,0x3ec43f6d,0xbec4bf6d,0xbec4bf6d,0x3ec43f6d,
  0,0,0,0,0xbf353f35,0x3f35bf35,0xbf353f35,0x3f35bf35,0xbf803f80,0xbf803f80,0xbf803f80,0xbf803f80,
  0xbf353f35,0x3f35bf35,0xbf353f35,0x3f35bf35,0xbf800000,0xbf800000,0x3f800000,0x3f800000,0xbec43f6d,0x3ec4bf6d,0x3ec4bf6d,0xbec43f6d,
  0x3f353f35,0x3f353f35,0xbf35bf35,0xbf35bf35,0x3f6dbec4,0xbf6d3ec4,0xbf6d3ec4,0x3f6dbec4,0,0,0,0,
  0x3f803f80,0xbf80bf80,0x3f803f80,0xbf80bf80,0,0,0,0,0xbf80bf80,0x3f803f80,0xbf80bf80,0x3f803f80,
  0x3f800000,0x3f800000,0xbf800000,0xbf800000,0xbec43f6d,0x3ec4bf6d,0x3ec4bf6d,0xbec43f6d,0xbf35bf35,0xbf35bf35,0x3f353f35,0x3f353f35,
  0x3f6dbec4,0xbf6d3ec4,0xbf6d3ec4,0x3f6dbec4,0,0,0,0,0xbf353f35,0x3f35bf35,0xbf353f35,0x3f35bf35,
  0x3f80bf80,0x3f80bf80,0x3f80bf80,0x3f80bf80,0xbf353f35,0x3f35bf35,0xbf353f35,0x3f35bf35,0xbf800000,0xbf800000,0x3f800000,0x3f800000,
  0x3f6d3ec4,0xbf6dbec4,0xbf6dbec4,0x3f6d3ec4,0xbf35bf35,0xbf35bf35,0x3f353f35,0x3f353f35,0x3ec43f6d,0xbec4bf6d,0xbec4bf6d,0x3ec43f6d,
  0x3f803f80,0x3f803f80,0xbf803f80,0xbf803f80,0x3f803f80,0x3f803f80,0xbf803f80,0xbf803f80,0x3f803f80,0x3f803f80,0xbf803f80,0xbf803f80,
  0x3f803f80,0x3f803f80,0xbf803f80,0xbf803f80,0x3f6d3f80,0x3ec43f35,0xbf6d3f80,0xbec43f35,0xbec40000,0xbf6dbf35,0x3ec40000,0x3f6dbf35,
  0xbf6dbf80,0xbec4bf35,0x3f6dbf80,0x3ec4bf35,0x3ec40000,0x3f6d3f35,0xbec40000,0xbf6d3f35,0x3f353f80,0xbf350000,0xbf353f80,0x3f350000,
  0xbf35bf80,0x3f350000,0x3f35bf80,0xbf350000,0x3f353f80,0xbf350000,0xbf353f80,0x3f350000,0xbf35bf80,0x3f350000,0x3f35bf80,0xbf350000,
  0x3ec43f80,0xbf6dbf35,0xbec43f80,0x3f6dbf35,0x3f6d0000,0xbec43f35,0xbf6d0000,0x3ec43f35,0xbec4bf80,0x3f6d3f35,0x3ec4bf80,0xbf6d3f35,
  0xbf6d0000,0x3ec4bf35,0x3f6d0000,0xbec4bf35,0x3f80,0xbf80,0x3f80,0xbf80,0x3f80,0xbf80,0x3f80,0xbf80,
  0x3f80,0xbf80,0x3f80,0xbf80,0x3f80,0xbf80,0x3f80,0xbf80,0xbec43f80,0x3f6dbf35,0x3ec43f80,0xbf6dbf35,
  0xbf6d0000,0x3ec43f35,0x3f6d0000,0xbec43f35,0x3ec4bf80,0xbf6d3f35,0xbec4bf80,0x3f6d3f35,0x3f6d0000,0xbec4bf35,0xbf6d0000,0x3ec4bf35,
  0xbf353f80,0x3f350000,0x3f353f80,0xbf350000,0x3f35bf80,0xbf350000,0xbf35bf80,0x3f350000,0xbf353f80,0x3f350000,0x3f353f80,0xbf350000,
  0x3f35bf80,0xbf350000,0xbf35bf80,0x3f350000,0xbf6d3f80,0xbec43f35,0x3f6d3f80,0x3ec43f35,0x3ec40000,0x3f6dbf35,0xbec40000,0xbf6dbf35,
  0x3f6dbf80,0x3ec4bf35,0xbf6dbf80,0xbec4bf35,0xbec40000,0xbf6d3f35,0x3ec40000,0x3f6d3f35,0x80008000,0x80008000,0x80008000,0x80008000,
  0x80008000,0x80008000,0x80008000,0x80008000,0x80008000,0x80008000,0x80008000,0x80008000,0x80008000,0x80008000,0x80008000,0x80008000,
  0xbec48000,0xbf6dbf35,0x3ec48000,0x3f6dbf35,0xbf6dbf80,0xbec4bf35,0x3f6dbf80,0x3ec4bf35,0x3ec48000,0x3f6d3f35,0xbec48000,0xbf6d3f35,
  0x3f6d3f80,0x3ec43f35,0xbf6d3f80,0xbec43f35,0xbf358000,0xbf35bf80,0x3f358000,0x3f35bf80,0x3f358000,0x3f353f80,0xbf358000,0xbf353f80,
  0xbf358000,0xbf35bf80,0x3f358000,0x3f35bf80,0x3f358000,0x3f353f80,0xbf358000,0xbf353f80,0xbf6d8000,0x3ec4bf35,0x3f6d8000,0xbec4bf35,
  0x3ec43f80,0xbf6dbf35,0xbec43f80,0x3f6dbf35,0x3f6d8000,0xbec43f35,0xbf6d8000,0x3ec43f35,0xbec4bf80,0x3f6d3f35,0x3ec4bf80,0xbf6d3f35,
  0xbf808000,0x3f808000,0x3f808000,0xbf808000,0xbf808000,0x3f808000,0x3f808000,0xbf808000,0xbf808000,0x3f808000,0x3f808000,0xbf808000,
  0xbf808000,0x3f808000,0x3f808000,0xbf808000,0xbf6d8000,0x3ec43f35,0x3f6d8000,0xbec43f35,0x3ec4bf80,0xbf6d3f35,0xbec4bf80,0x3f6d3f35,
  0x3f6d8000,0xbec4bf35,0xbf6d8000,0x3ec4bf35,0xbec43f80,0x3f6dbf35,0x3ec43f80,0xbf6dbf35,0xbf358000,0xbf353f80,0x3f358000,0x3f353f80,
  0x3f358000,0x3f35bf80,0xbf358000,0xbf35bf80,0xbf358000,0xbf353f80,0x3f358000,0x3f353f80,0x3f358000,0x3f35bf80,0xbf358000,0xbf35bf80,
  0xbec48000,0xbf6d3f35,0x3ec48000,0x3f6d3f35,0xbf6d3f80,0xbec43f35,0x3f6d3f80,0x3ec43f35,0x3ec48000,0x3f6dbf35,0xbec48000,0xbf6dbf35,
  0x3f6dbf80,0x3ec4bf35,0xbf6dbf80,0xbec4bf35,0,0,0,0,0,0,0,0,
  0,0,0,0,0,0,0,0,0x3ec40000,0x3f6d3f35,0xbec40000,0xbf6d3f35,
  0x3f6d3f80,0x3ec43f35,0xbf6d3f80,0xbec43f35,0xbec40000,0xbf6dbf35,0x3ec40000,0x3f6dbf35,0xbf6dbf80,0xbec4bf35,0x3f6dbf80,0x3ec4bf35,
  0x3f350000,0x3f353f80,0xbf350000,0xbf353f80,0xbf350000,0xbf35bf80,0x3f350000,0x3f35bf80,0x3f350000,0x3f353f80,0xbf350000,0xbf353f80,
  0xbf350000,0xbf35bf80,0x3f350000,0x3f35bf80,0x3f6d0000,0xbec43f35,0xbf6d0000,0x3ec43f35,0xbec4bf80,0x3f6d3f35,0x3ec4bf80,0xbf6d3f35,
  0xbf6d0000,0x3ec4bf35,0x3f6d0000,0xbec4bf35,0x3ec43f80,0xbf6dbf35,0xbec43f80,0x3f6dbf35,0x3f800000,0xbf800000,0xbf800000,0x3f800000,
  0x3f800000,0xbf800000,0xbf800000,0x3f800000,0x3f800000,0xbf800000,0xbf800000,0x3f800000,0x3f800000,0xbf800000,0xbf800000,0x3f800000,
  0x3f6d0000,0xbec4bf35,0xbf6d0000,0x3ec4bf35,0xbec43f80,0x3f6dbf35,0x3ec43f80,0xbf6dbf35,0xbf6d0000,0x3ec43f35,0x3f6d0000,0xbec43f35,
  0x3ec4bf80,0xbf6d3f35,0xbec4bf80,0x3f6d3f35,0x3f350000,0x3f35bf80,0xbf350000,0xbf35bf80,0xbf350000,0xbf353f80,0x3f350000,0x3f353f80,
  0x3f350000,0x3f35bf80,0xbf350000,0xbf35bf80,0xbf350000,0xbf353f80,0x3f350000,0x3f353f80,0x3ec40000,0x3f6dbf35,0xbec40000,0xbf6dbf35,
  0x3f6dbf80,0x3ec4bf35,0xbf6dbf80,0xbec4bf35,0xbec40000,0xbf6d3f35,0x3ec40000,0x3f6d3f35,0xbf6d3f80,0xbec43f35,0x3f6d3f80,0x3ec43f35,
  0x3f800000,0x80000000,0x3f800000,0x80000000,0x3f800000,0x80000000,0x3f800000,0x80000000,0x3f800000,0x80000000,0x3f800000,0x80000000,
  0x3f800000,0x80000000,0x3f800000,0x80000000,0x3f800000,0x80000000,0x3f7fec43,0xbcc90ab0,0x3f7ec46d,0xbdc8bd36,0x3f7e1324,0xbdfab273,
  0x3f7b14be,0xbe47c5c2,0x3f79c79d,0xbe605c13,0x3f74fa0b,0xbe94a031,0x3f731447,0xbea09ae5,0x3f800000,0x80000000,0x3f7fb10f,0xbd48fb30,
  0x3f7b14be,0xbe47c5c2,0x3f7853f8,0xbe78cfcc,0x3f6c835e,0xbec3ef15,0x3f676bd8,0xbedae880,0x3f54db31,0xbf0e39da,0x3f4d9f02,0xbf187fc0,
  0x3f800000,0x80000000,0x3f7f4e6d,0xbd96a905,0x3f74fa0b,0xbe94a031,0x3f6ed89e,0xbeb8442a,0x3f54db31,0xbf0e39da,0x3f49d112,0xbf1d7fd1,
  0x3f226799,0xbf45e403,0x3f13682a,0xbf514d3d,0x3f800000,0x80000000,0x3f7ec46d,0xbdc8bd36,0x3f6c835e,0xbec3ef15,0x3f61c598,0xbef15aea,
  0x3f3504f3,0xbf3504f3,0x3f226799,0xbf45e403,0x3ec3ef15,0xbf6c835e,0x3e94a031,0xbf74fa0b,0x3f800000,0x80000000,0x3f7e1324,0xbdfab273,
  0x3f61c598,0xbef15aea,0x3f514d3d,0xbf13682a,0x3f0e39da,0xbf54db31,0x3ee63375,0xbf64aa59,0x3dc8bd36,0xbf7ec46d,0xbcc90ab0,0xbf7fec43,
  0x3f800000,0x80000000,0x3f7d3aac,0xbe164083,0x3f54db31,0xbf0e39da,0x3f3daef9,0xbf2beb4a,0x3ec3ef15,0xbf6c835e,0x3e78cfcc,0xbf7853f8,
  0xbe47c5c2,0xbf7b14be,0xbeac7cd4,0xbf710908,0x3f800000,0x80000000,0x3f7c3b28,0xbe2f10a2,0x3f45e403,0xbf226799,0x3f273656,0xbf41d870,
  0x3e47c5c2,0xbf7b14be,0x3cc90ab0,0xbf7fec43,0xbef15aea,0xbf61c598,0xbf1d7fd1,0xbf49d112,0x3f800000,0x80000000,0x3f800000,0x80000000,
  0x3f800000,0x80000000,0x3f800000,0x80000000,0x3f800000,0x80000000,0x3f800000,0x80000000,0x3f800000,0x80000000,0x3f800000,0x80000000,
  0x3f7fb10f,0xbd48fb30,0x3f7f4e6d,0xbd96a905,0x3f7d3aac,0xbe164083,0x3f7c3b28,0xbe2f10a2,0x3f7853f8,0xbe78cfcc,0x3f76ba07,0xbe888e93,
  0x3f710908,0xbeac7cd4,0x3f6ed89e,0xbeb8442a,0x3f7ec46d,0xbdc8bd36,0x3f7d3aac,0xbe164083,0x3f74fa0b,0xbe94a031,0x3f710908,0xbeac7cd4,
  0x3f61c598,0xbef15aea,0x3f5b941a,0xbf039c3d,0x3f45e403,0xbf226799,0x3f3daef9,0xbf2beb4a,0x3f7d3aac,0xbe164083,0x3f79c79d,0xbe605c13,
  0x3f676bd8,0xbedae880,0x3f5ebe05,0xbefc5d27,0x3f3daef9,0xbf2beb4a,0x3f3085bb,0xbf396842,0x3f039c3d,0xbf5b941a,0x3ee63375,0xbf64aa59,
  0x3f7b14be,0xbe47c5c2,0x3f74fa0b,0xbe94a031,0x3f54db31,0xbf0e39da,0x3f45e403,0xbf226799,0x3f0e39da,0xbf54db31,0x3ef15aea,0xbf61c598,
  0x3e47c5c2,0xbf7b14be,0x3dc8bd36,0xbf7ec46d,0x3f7853f8,0xbe78cfcc,0x3f6ed89e,0xbeb8442a,0x3f3daef9,0xbf2beb4a,0x3f273656,0xbf41d870,
  0x3eac7cd4,0xbf710908,0x3e605c13,0xbf79c79d,0xbe164083,0xbf7d3aac,0xbe888e93,0xbf76ba07,0x3f74fa0b,0xbe94a031,0x3f676bd8,0xbedae880,
  0x3f226799,0xbf45e403,0x3f039c3d,0xbf5b941a,0x3dc8bd36,0xbf7ec46d,0xbd48fb30,0xbf7fb10f,0xbef15aea,0xbf61c598,0xbf187fc0,0xbf4d9f02,
  0x3f710908,0xbeac7cd4,0x3f5ebe05,0xbefc5d27,0x3f039c3d,0xbf5b941a,0x3eb8442a,0xbf6ed89e,0xbe164083,0xbf7d3aac,0xbea09ae5,0xbf731447,
  0xbf3daef9,0xbf2beb4a,0xbf584853,0xbf08f59b,0x3f800000,0x80000000,0x3f7b14be,0xbe47c5c2,0x3f3504f3,0xbf3504f3,0x3f0e39da,0xbf54db31,
  0,0xbf800000,0xbe47c5c2,0xbf7b14be,0xbf3504f3,0xbf3504f3,0xbf54db31,0xbf0e39da,0x3f800000,0x80000000,0x3f79c79d,0xbe605c13,
  0x3f226799,0xbf45e403,0x3ee63375,0xbf64aa59,0xbe47c5c2,0xbf7b14be,0xbecf7bca,0xbf6a09a7,0xbf61c598,0xbef15aea,0xbf76ba07,0xbe888e93,
  0x3f800000,0x80000000,0x3f7853f8,0xbe78cfcc,0x3f0e39da,0xbf54db31,0x3eac7cd4,0xbf710908,0xbec3ef15,0xbf6c835e,0xbf187fc0,0xbf4d9f02,
  0xbf7b14be,0xbe47c5c2,0xbf7fb10f,0x3d48fb30,0x3f800000,0x80000000,0x3f76ba07,0xbe888e93,0x3ef15aea,0xbf61c598,0x3e605c13,0xbf79c79d,
  0xbf0e39da,0xbf54db31,0xbf41d870,0xbf273656,0xbf7ec46d,0x3dc8bd36,0xbf6ed89e,0x3eb8442a,0x3f800000,0x80000000,0x3f74fa0b,0xbe94a031,
  0x3ec3ef15,0xbf6c835e,0x3dc8bd36,0xbf7ec46d,0xbf3504f3,0xbf3504f3,0xbf61c598,0xbef15aea,0xbf6c835e,0x3ec3ef15,0xbf45e403,0x3f226799,
  0x3f800000,0x80000000,0x3f731447,0xbea09ae5,0x3e94a031,0xbf74fa0b,0xbcc90ab0,0xbf7fec43,0xbf54db31,0xbf0e39da,0xbf76ba07,0xbe888e93,
  0xbf45e403,0x3f226799,0xbf08f59b,0x3f584853,0x3f800000,0x80000000,0x3f710908,0xbeac7cd4,0x3e47c5c2,0xbf7b14be,0xbe164083,0xbf7d3aac,
  0xbf6c835e,0xbec3ef15,0xbf7fb10f,0xbd48fb30,0xbf0e39da,0x3f54db31,0xbe78cfcc,0x3f7853f8,0x3f800000,0x80000000,0x3f6ed89e,0xbeb8442a,
  0x3dc8bd36,0xbf7ec46d,0xbe888e93,0xbf76ba07,0xbf7b14be,0xbe47c5c2,0xbf7c3b28,0x3e2f10a2,0xbe94a031,0x3f74fa0b,0x3d96a905,0x3f7f4e6d,
  0x3f6c835e,0xbec3ef15,0x3f54db31,0xbf0e39da,0x3ec3ef15,0xbf6c835e,0x3e47c5c2,0xbf7b14be,0xbec3ef15,0xbf6c835e,0xbf0e39da,0xbf54db31,
  0xbf6c835e,0xbec3ef15,0xbf7b14be,0xbe47c5c2,0x3f676bd8,0xbedae880,0x3f49d112,0xbf1d7fd1,0x3e78cfcc,0xbf7853f8,0x3cc90ab0,0xbf7fec43,
  0xbf187fc0,0xbf4d9f02,0xbf41d870,0xbf273656,0xbf7fb10f,0xbd48fb30,0xbf7c3b28,0x3e2f10a2,0x3f61c598,0xbef15aea,0x3f3daef9,0xbf2beb4a,
  0x3dc8bd36,0xbf7ec46d,0xbe164083,0xbf7d3aac,0xbf45e403,0xbf226799,0xbf676bd8,0xbedae880,0xbf74fa0b,0x3e94a031,0xbf5b941a,0x3f039c3d,
  0x3f5b941a,0xbf039c3d,0x3f3085bb,0xbf396842,0xbd48fb30,0xbf7fb10f,0xbea09ae5,0xbf731447,0xbf676bd8,0xbedae880,0xbf7c3b28,0xbe2f10a2,
  0xbf4d9f02,0x3f187fc0,0xbf1d7fd1,0x3f49d112,0x3f54db31,0xbf0e39da,0x3f226799,0xbf45e403,0xbe47c5c2,0xbf7b14be,0xbef15aea,0xbf61c598,
  0xbf7b14be,0xbe47c5c2,0xbf7ec46d,0x3dc8bd36,0xbf0e39da,0x3f54db31,0xbe94a031,0x3f74fa0b,0x3f4d9f02,0xbf187fc0,0x3f13682a,0xbf514d3d,
  0xbeac7cd4,0xbf710908,0xbf1d7fd1,0xbf49d112,0xbf7fb10f,0x3d48fb30,0xbf6ed89e,0x3eb8442a,0xbe78cfcc,0x3f7853f8,0x3d96a905,0x3f7f4e6d,
  0x3f45e403,0xbf226799,0x3f039c3d,0xbf5b941a,0xbef15aea,0xbf61c598,0xbf3daef9,0xbf2beb4a,0xbf74fa0b,0x3e94a031,0xbf4d9f02,0x3f187fc0,
  0x3dc8bd36,0x3f7ec46d,0x3edae880,0x3f676bd8,0x3f3daef9,0xbf2beb4a,0x3ee63375,0xbf64aa59,0xbf187fc0,0xbf4d9f02,0xbf584853,0xbf08f59b,
  0xbf5b941a,0x3f039c3d,0xbf1d7fd1,0x3f49d112,0x3edae880,0x3f676bd8,0x3f396842,0x3f3085bb,0x3f80,0x3f80,0x3f80,0x3f80,
  0x3f80,0x3f80,0xbf80,0xbf80,0x3f80,0x3f80,0x3f80,0x3f80,0x3f80,0x3f80,0xbf80,0xbf80,
  0x3f808000,0x3f808000,0x3f808000,0x3f808000,0x3f808000,0x3f808000,0xbf808000,0xbf808000,0x3f808000,0x3f808000,0x3f808000,0x3f808000,
  0x3f808000,0x3f808000,0xbf808000,0xbf808000,0x3f80,0xbf80,0x3f80,0xbf80,0x3f353f35,0xbf35bf35,0xbf35bf35,0x3f353f35,
  0x3f800000,0xbf800000,0x3f800000,0xbf800000,0x3f35bf35,0xbf353f35,0xbf353f35,0x3f35bf35,0x3f808000,0xbf808000,0x3f808000,0xbf808000,
  0x3f35bf35,0xbf353f35,0xbf353f35,0x3f35bf35,0xbf80,0x3f80,0xbf80,0x3f80,0xbf35bf35,0x3f353f35,0x3f353f35,0xbf35bf35,
  0x3f80,0x3f80,0x3f80,0x3f80,0x3f800000,0x3f800000,0xbf800000,0xbf800000,0xbf80,0xbf80,0xbf80,0xbf80,
  0xbf800000,0xbf800000,0x3f800000,0x3f800000,0x3f808000,0x3f808000,0x3f808000,0x3f808000,0xbf80,0xbf80,0x3f80,0x3f80,
  0xbf808000,0xbf808000,0xbf808000,0xbf808000,0x3f80,0x3f80,0xbf80,0xbf80,0x3f80,0xbf80,0x3f80,0xbf80,
  0x3f35bf35,0xbf353f35,0xbf353f35,0x3f35bf35,0xbf800000,0x3f800000,0xbf800000,0x3f800000,0x3f353f35,0xbf35bf35,0xbf35bf35,0x3f353f35,
  0x3f808000,0xbf808000,0x3f808000,0xbf808000,0xbf35bf35,0x3f353f35,0x3f353f35,0xbf35bf35,0x3f80,0xbf80,0x3f80,0xbf80,
  0x3f35bf35,0xbf353f35,0xbf353f35,0x3f35bf35,0x3f80,0x3f80,0x3f80,0x3f80,0x3f80,0x3f80,0x3f800000,0x3f800000,
  0x3f80,0x3f80,0xbf80,0xbf80,0x3f80,0x3f80,0xbf800000,0xbf800000,0x3f808000,0x3f808000,0x3f808000,0x3f808000,
  0x3f808000,0x3f808000,0xbf80,0xbf80,0x3f808000,0x3f808000,0xbf808000,0xbf808000,0x3f808000,0x3f808000,0x3f80,0x3f80,
  0x3f80,0x3f800000,0x3f80,0x3f800000,0x3ec43f6d,0x3f6dbec4,0x3f6dbec4,0xbec4bf6d,0x3f353f35,0x3f35bf35,0xbf35bf35,0xbf353f35,
  0x3f6d3ec4,0x3ec4bf6d,0xbec43f6d,0x3f6d3ec4,0x3f808000,0xbf80,0x3f808000,0xbf80,0x3f6dbec4,0xbec4bf6d,0xbec4bf6d,0xbf6d3ec4,
  0x3f35bf35,0xbf35bf35,0xbf353f35,0x3f353f35,0x3ec4bf6d,0xbf6dbec4,0x3f6d3ec4,0x3ec4bf6d,0x3f80,0xbf80,0x3f80,0xbf80,
  0x3f353f35,0xbf35bf35,0x3f35bf35,0xbf353f35,0x3f800000,0xbf800000,0xbf800000,0x3f800000,0x3f35bf35,0xbf353f35,0x3f353f35,0xbf35bf35,
  0x3f808000,0xbf808000,0x3f808000,0xbf808000,0x3f35bf35,0xbf353f35,0xbf35bf35,0x3f353f35,0xbf80,0x3f80,0x3f80,0xbf80,
  0xbf35bf35,0x3f353f35,0x3f35bf35,0xbf353f35,0x3f80,0xbf800000,0x3f80,0xbf800000,0x3f6d3ec4,0xbec43f6d,0x3ec4bf6d,0x3f6d3ec4,
  0x3f35bf35,0x3f353f35,0xbf353f35,0xbf35bf35,0xbec4bf6d,0x3f6dbec4,0x3f6dbec4,0x3ec43f6d,0x3f808000,0x3f80,0x3f808000,0x3f80,
  0x3ec4bf6d,0x3f6d3ec4,0xbf6dbec4,0x3ec4bf6d,0xbf35bf35,0x3f35bf35,0x3f353f35,0xbf353f35,0xbf6d3ec4,0xbec4bf6d,0xbec4bf6d,0x3f6dbec4,
  0x3f80,0x3f80,0x3f80,0x3f80,0xbf80,0xbf80,0xbf800000,0xbf800000,0x3f80,0x3f80,0xbf80,0xbf80,
  0xbf80,0xbf80,0x3f800000,0x3f800000,0x3f808000,0x3f808000,0x3f808000,0x3f808000,0xbf808000,0xbf808000,0x3f80,0x3f80,
  0x3f808000,0x3f808000,0xbf808000,0xbf808000,0xbf808000,0xbf808000,0xbf80,0xbf80,0x3f80,0x3f800000,0x3f80,0x3f800000,
  0xbec4bf6d,0xbf6d3ec4,0xbf6d3ec4,0x3ec43f6d,0x3f353f35,0x3f35bf35,0xbf35bf35,0xbf353f35,0xbf6dbec4,0xbec43f6d,0x3ec4bf6d,0xbf6dbec4,
  0x3f808000,0xbf80,0x3f808000,0xbf80,0xbf6d3ec4,0x3ec43f6d,0x3ec43f6d,0x3f6dbec4,0x3f35bf35,0xbf35bf35,0xbf353f35,0x3f353f35,
  0xbec43f6d,0x3f6d3ec4,0xbf6dbec4,0xbec43f6d,0x3f80,0xbf80,0x3f80,0xbf80,0xbf35bf35,0x3f353f35,0xbf353f35,0x3f35bf35,
  0x3f800000,0xbf800000,0xbf800000,0x3f800000,0xbf353f35,0x3f35bf35,0xbf35bf35,0x3f353f35,0x3f808000,0xbf808000,0x3f808000,0xbf808000,
  0xbf353f35,0x3f35bf35,0x3f353f35,0xbf35bf35,0xbf80,0x3f80,0x3f80,0xbf80,0x3f353f35,0xbf35bf35,0xbf353f35,0x3f35bf35,
  0x3f80,0xbf800000,0x3f80,0xbf800000,0xbf6dbec4,0x3ec4bf6d,0xbec43f6d,0xbf6dbec4,0x3f35bf35,0x3f353f35,0xbf353f35,0xbf35bf35,
  0x3ec43f6d,0xbf6d3ec4,0xbf6d3ec4,0xbec4bf6d,0x3f808000,0x3f80,0x3f808000,0x3f80,0xbec43f6d,0xbf6dbec4,0x3f6d3ec4,0xbec43f6d,
  0xbf35bf35,0x3f35bf35,0x3f353f35,0xbf353f35,0x3f6dbec4,0x3ec43f6d,0x3ec43f6d,0xbf6d3ec4,0x3f80,0x3f80,0x3f80,0x3f80,
  0x3f80,0x3f80,0x3f800000,0x3f800000,0x3f80,0x3f80,0xbf80,0xbf80,0x3f80,0x3f80,0xbf800000,0xbf800000,
  0x3f808000,0x3f808000,0x3f808000,0x3f808000,0x3f808000,0x3f808000,0xbf80,0xbf80,0x3f808000,0x3f808000,0xbf808000,0xbf808000,
  0x3f808000,0x3f808000,0x3f80,0x3f80,0xbf80,0xbf800000,0xbf80,0xbf800000,0xbec4bf6d,0xbf6d3ec4,0xbf6d3ec4,0x3ec43f6d,
  0xbf35bf35,0xbf353f35,0x3f353f35,0x3f35bf35,0xbf6dbec4,0xbec43f6d,0x3ec4bf6d,0xbf6dbec4,0xbf808000,0x3f80,0xbf808000,0x3f80,
  0xbf6d3ec4,0x3ec43f6d,0x3ec43f6d,0x3f6dbec4,0xbf353f35,0x3f353f35,0x3f35bf35,0xbf35bf35,0xbec43f6d,0x3f6d3ec4,0xbf6dbec4,0xbec43f6d,
  0x3f80,0xbf80,0x3f80,0xbf80,0x3f353f35,0xbf35bf35,0x3f35bf35,0xbf353f35,0x3f800000,0xbf800000,0xbf800000,0x3f800000,
  0x3f35bf35,0xbf353f35,0x3f353f35,0xbf35bf35,0x3f808000,0xbf808000,0x3f808000,0xbf808000,0x3f35bf35,0xbf353f35,0xbf35bf35,0x3f353f35,
  0xbf80,0x3f80,0x3f80,0xbf80,0xbf35bf35,0x3f353f35,0x3f35bf35,0xbf353f35,0xbf80,0x3f800000,0xbf80,0x3f800000,
  0xbf6dbec4,0x3ec4bf6d,0xbec43f6d,0xbf6dbec4,0xbf353f35,0xbf35bf35,0x3f35bf35,0x3f353f35,0x3ec43f6d,0xbf6d3ec4,0xbf6d3ec4,0xbec4bf6d,
  0xbf808000,0xbf80,0xbf808000,0xbf80,0xbec43f6d,0xbf6dbec4,0x3f6d3ec4,0xbec43f6d,0x3f353f35,0xbf353f35,0xbf35bf35,0x3f35bf35,
  0x3f6dbec4,0x3ec43f6d,0x3ec43f6d,0xbf6d3ec4,0x3f80,0x3f80,0x3f80,0x3f80,0xbf80,0xbf80,0xbf800000,0xbf800000,
  0x3f80,0x3f80,0xbf80,0xbf80,0xbf80,0xbf80,0x3f800000,0x3f800000,0x3f808000,0x3f808000,0x3f808000,0x3f808000,
  0xbf808000,0xbf808000,0x3f80,0x3f80,0x3f808000,0x3f808000,0xbf808000,0xbf808000,0xbf808000,0xbf808000,0xbf80,0xbf80,
  0xbf80,0xbf800000,0xbf80,0xbf800000,0x3ec43f6d,0x3f6dbec4,0x3f6dbec4,0xbec4bf6d,0xbf35bf35,0xbf353f35,0x3f353f35,0x3f35bf35,
  0x3f6d3ec4,0x3ec4bf6d,0xbec43f6d,0x3f6d3ec4,0xbf808000,0x3f80,0xbf808000,0x3f80,0x3f6dbec4,0xbec4bf6d,0xbec4bf6d,0xbf6d3ec4,
  0xbf353f35,0x3f353f35,0x3f35bf35,0xbf35bf35,0x3ec4bf6d,0xbf6dbec4,0x3f6d3ec4,0x3ec4bf6d,0x3f80,0xbf80,0x3f80,0xbf80,
  0xbf35bf35,0x3f353f35,0xbf353f35,0x3f35bf35,0x3f800000,0xbf800000,0xbf800000,0x3f800000,0xbf353f35,0x3f35bf35,0xbf35bf35,0x3f353f35,
  0x3f808000,0xbf808000,0x3f808000,0xbf808000,0xbf353f35,0x3f35bf35,0x3f353f35,0xbf35bf35,0xbf80,0x3f80,0x3f80,0xbf80,
  0x3f353f35,0xbf35bf35,0xbf353f35,0x3f35bf35,0xbf80,0x3f800000,0xbf80,0x3f800000,0x3f6d3ec4,0xbec43f6d,0x3ec4bf6d,0x3f6d3ec4,
  0xbf353f35,0xbf35bf35,0x3f35bf35,0x3f353f35,0xbec4bf6d,0x3f6dbec4,0x3f6dbec4,0x3ec43f6d,0xbf808000,0xbf80,0xbf808000,0xbf80,
  0x3ec4bf6d,0x3f6d3ec4,0xbf6dbec4,0x3ec4bf6d,0x3f353f35,0xbf353f35,0xbf35bf35,0x3f35bf35,0xbf6d3ec4,0xbec4bf6d,0xbec4bf6d,0x3f6dbec4,
  0x3f80,0x3f80,0x3e483f7b,0x3e483f7b,0x3f80,0x3f80,0x3f7bbe48,0x3f7bbe48,0x3f80,0x3f80,0xbe48bf7b,0xbe48bf7b,
  0x3f80,0x3f80,0xbf7b3e48,0xbf7b3e48,0x3f808000,0x3f808000,0x3f7bbe48,0x3f7bbe48,0x3f808000,0x3f808000,0xbe48bf7b,0xbe48bf7b,
  0x3f808000,0x3f808000,0xbf7b3e48,0xbf7b3e48,0x3f808000,0x3f808000,0x3e483f7b,0x3e483f7b,0x3d493f80,0x3f80bd49,0x3e793f78,0x3f78be79,
  0x3edb3f67,0x3f67bedb,0x3f4ebf18,0xbf18bf4e,0x3f3e3f2c,0x3f2cbf3e,0xbf5cbf04,0xbf043f5c,0x3f713eac,0x3eacbf71,0xbe163f7d,0x3f7d3e16,
  0x3f80bd49,0xbd49bf80,0x3f78be79,0xbe79bf78,0x3f67bedb,0xbedbbf67,0xbf18bf4e,0xbf4e3f18,0x3f2cbf3e,0xbf3ebf2c,0xbf043f5c,0x3f5c3f04,
  0x3eacbf71,0xbf71beac,0x3f7d3e16,0x3e16bf7d,0x3dc93f7f,0xbdc9bf7f,0x3e953f75,0xbe95bf75,0x3f463f22,0xbf46bf22,0x3ef1bf62,0xbef13f62,
  0x3f7fbdc9,0xbf7f3dc9,0xbf753e95,0x3f75be95,0x3f22bf46,0xbf223f46,0x3f623ef1,0xbf62bef1,0x3f7fbdc9,0xbf7f3dc9,0x3f75be95,0xbf753e95,
  0x3f22bf46,0xbf223f46,0xbf62bef1,0x3f623ef1,0xbdc9bf7f,0x3dc93f7f,0x3e953f75,0xbe95bf75,0xbf46bf22,0x3f463f22,0x3ef1bf62,0xbef13f62,
  0x3e163f7d,0xbf7d3e16,0x3eac3f71,0xbf713eac,0x3f783e79,0xbe793f78,0x3d49bf80,0x3f803d49,0x3f18bf4e,0x3f4e3f18,0xbedb3f67,0xbf67bedb,
  0xbf04bf5c,0x3f5cbf04,0x3f3ebf2c,0x3f2c3f3e,0x3f7dbe16,0x3e163f7d,0x3f71beac,0x3eac3f71,0x3e79bf78,0x3f783e79,0xbf80bd49,0x3d49bf80,
  0xbf4ebf18,0x3f18bf4e,0x3f673edb,0xbedb3f67,0xbf5c3f04,0xbf04bf5c,0xbf2cbf3e,0x3f3ebf2c,0x3ec43f6d,0x3ec43f6d,0x3f0e3f55,0x3f0e3f55,
  0xbec4bf6d,0xbec4bf6d,0xbf553f0e,0xbf553f0e,0x3ec43f6d,0x3ec43f6d,0xbf0ebf55,0xbf0ebf55,0xbec4bf6d,0xbec4bf6d,0x3f55bf0e,0x3f55bf0e,
  0x3f6dbec4,0x3f6dbec4,0x3f55bf0e,0x3f55bf0e,0xbf6d3ec4,0xbf6d3ec4,0x3f0e3f55,0x3f0e3f55,0x3f6dbec4,0x3f6dbec4,0xbf553f0e,0xbf553f0e,
  0xbf6d3ec4,0xbf6d3ec4,0xbf0ebf55,0xbf0ebf55,0x3edb3f67,0x3f67bedb,0x3f183f4e,0x3f4ebf18,0xbf3ebf2c,0xbf2c3f3e,0xbf043f5c,0x3f5c3f04,
  0x3f713eac,0x3eacbf71,0xbf7dbe16,0xbe163f7d,0xbf803d49,0x3d493f80,0xbe79bf78,0xbf783e79,0x3f67bedb,0xbedbbf67,0x3f4ebf18,0xbf18bf4e,
  0xbf2c3f3e,0x3f3e3f2c,0x3f5c3f04,0x3f04bf5c,0x3eacbf71,0xbf71beac,0xbe163f7d,0x3f7d3e16,0x3d493f80,0x3f80bd49,0xbf783e79,0x3e793f78,
  0x3ef13f62,0xbef1bf62,0x3f223f46,0xbf22bf46,0xbf75be95,0x3f753e95,0xbdc93f7f,0x3dc9bf7f,0x3f62bef1,0xbf623ef1,0xbf463f22,0x3f46bf22,
  0xbe953f75,0x3e95bf75,0xbf7fbdc9,0x3f7f3dc9,0x3f62bef1,0xbf623ef1,0x3f46bf22,0xbf463f22,0xbe953f75,0x3e95bf75,0x3f7f3dc9,0xbf7fbdc9,
  0xbef1bf62,0x3ef13f62,0x3f223f46,0xbf22bf46,0x3f753e95,0xbf75be95,0xbdc93f7f,0x3dc9bf7f,0x3f043f5c,0xbf5c3f04,0x3f2c3f3e,0xbf3e3f2c,
  0xbf7d3e16,0xbe16bf7d,0x3eac3f71,0xbf713eac,0x3e79bf78,0x3f783e79,0xbd493f80,0xbf80bd49,0x3f4e3f18,0xbf183f4e,0xbedb3f67,0xbf67bedb,
  0x3f5cbf04,0x3f043f5c,0x3f3ebf2c,0x3f2c3f3e,0x3e163f7d,0xbf7d3e16,0x3f71beac,0x3eac3f71,0xbf78be79,0x3e79bf78,0x3f803d49,0xbd493f80,
  0x3f18bf4e,0x3f4e3f18,0x3f673edb,0xbedb3f67,0x3f80,0x3f80,0x3e483f7b,0x3e483f7b,0x3f80,0x3f80,0x3f7bbe48,0x3f7bbe48,
  0x3f80,0x3f80,0xbe48bf7b,0xbe48bf7b,0x3f80,0x3f80,0xbf7b3e48,0xbf7b3e48,0x3f808000,0x3f808000,0x3f7bbe48,0x3f7bbe48,
  0x3f808000,0x3f808000,0xbe48bf7b,0xbe48bf7b,0x3f808000,0x3f808000,0xbf7b3e48,0xbf7b3e48,0x3f808000,0x3f808000,0x3e483f7b,0x3e483f7b,
  0xbd49bf80,0xbf803d49,0xbe79bf78,0xbf783e79,0xbedbbf67,0xbf673edb,0xbf4e3f18,0x3f183f4e,0xbf3ebf2c,0xbf2c3f3e,0x3f5c3f04,0x3f04bf5c,
  0xbf71beac,0xbeac3f71,0x3e16bf7d,0xbf7dbe16,0xbf803d49,0x3d493f80,0xbf783e79,0x3e793f78,0xbf673edb,0x3edb3f67,0x3f183f4e,0x3f4ebf18,
  0xbf2c3f3e,0x3f3e3f2c,0x3f04bf5c,0xbf5cbf04,0xbeac3f71,0x3f713eac,0xbf7dbe16,0xbe163f7d,0x3dc93f7f,0xbdc9bf7f,0x3e953f75,0xbe95bf75,
  0x3f463f22,0xbf46bf22,0x3ef1bf62,0xbef13f62,0x3f7fbdc9,0xbf7f3dc9,0xbf753e95,0x3f75be95,0x3f22bf46,0xbf223f46,0x3f623ef1,0xbf62bef1,
  0x3f7fbdc9,0xbf7f3dc9,0x3f75be95,0xbf753e95,0x3f22bf46,0xbf223f46,0xbf62bef1,0x3f623ef1,0xbdc9bf7f,0x3dc93f7f,0x3e953f75,0xbe95bf75,
  0xbf46bf22,0x3f463f22,0x3ef1bf62,0xbef13f62,0xbe16bf7d,0x3f7dbe16,0xbeacbf71,0x3f71beac,0xbf78be79,0x3e79bf78,0xbd493f80,0xbf80bd49,
  0xbf183f4e,0xbf4ebf18,0x3edbbf67,0x3f673edb,0x3f043f5c,0xbf5c3f04,0xbf3e3f2c,0xbf2cbf3e,0xbf7d3e16,0xbe16bf7d,0xbf713eac,0xbeacbf71,
  0xbe793f78,0xbf78be79,0x3f803d49,0xbd493f80,0x3f4e3f18,0xbf183f4e,0xbf67bedb,0x3edbbf67,0x3f5cbf04,0x3f043f5c,0x3f2c3f3e,0xbf3e3f2c,
  0x3ec43f6d,0x3ec43f6d,0x3f0e3f55,0x3f0e3f55,0xbec4bf6d,0xbec4bf6d,0xbf553f0e,0xbf553f0e,0x3ec43f6d,0x3ec43f6d,0xbf0ebf55,0xbf0ebf55,
  0xbec4bf6d,0xbec4bf6d,0x3f55bf0e,0x3f55bf0e,0x3f6dbec4,0x3f6dbec4,0x3f55bf0e,0x3f55bf0e,0xbf6d3ec4,0xbf6d3ec4,0x3f0e3f55,0x3f0e3f55,
  0x3f6dbec4,0x3f6dbec4,0xbf553f0e,0xbf553f0e,0xbf6d3ec4,0xbf6d3ec4,0xbf0ebf55,0xbf0ebf55,0xbedbbf67,0xbf673edb,0xbf18bf4e,0xbf4e3f18,
  0x3f3e3f2c,0x3f2cbf3e,0x3f04bf5c,0xbf5cbf04,0xbf71beac,0xbeac3f71,0x3f7d3e16,0x3e16bf7d,0x3f80bd49,0xbd49bf80,0x3e793f78,0x3f78be79,
  0xbf673edb,0x3edb3f67,0xbf4e3f18,0x3f183f4e,0x3f2cbf3e,0xbf3ebf2c,0xbf5cbf04,0xbf043f5c,0xbeac3f71,0x3f713eac,0x3e16bf7d,0xbf7dbe16,
  0xbd49bf80,0xbf803d49,0x3f78be79,0xbe79bf78,0x3ef13f62,0xbef1bf62,0x3f223f46,0xbf22bf46,0xbf75be95,0x3f753e95,0xbdc93f7f,0x3dc9bf7f,
  0x3f62bef1,0xbf623ef1,0xbf463f22,0x3f46bf22,0xbe953f75,0x3e95bf75,0xbf7fbdc9,0x3f7f3dc9,0x3f62bef1,0xbf623ef1,0x3f46bf22,0xbf463f22,
  0xbe953f75,0x3e95bf75,0x3f7f3dc9,0xbf7fbdc9,0xbef1bf62,0x3ef13f62,0x3f223f46,0xbf22bf46,0x3f753e95,0xbf75be95,0xbdc93f7f,0x3dc9bf7f,
  0xbf04bf5c,0x3f5cbf04,0xbf2cbf3e,0x3f3ebf2c,0x3f7dbe16,0x3e163f7d,0xbeacbf71,0x3f71beac,0xbe793f78,0xbf78be79,0x3d49bf80,0x3f803d49,
  0xbf4ebf18,0x3f18bf4e,0x3edbbf67,0x3f673edb,0xbf5c3f04,0xbf04bf5c,0xbf3e3f2c,0xbf2cbf3e,0xbe16bf7d,0x3f7dbe16,0xbf713eac,0xbeacbf71,
  0x3f783e79,0xbe793f78,0xbf80bd49,0x3d49bf80,0xbf183f4e,0xbf4ebf18,0xbf67bedb,0x3edbbf67,0x3f80,0x3f80,0x3ec43f6d,0x3ec43f6d,
  0x3f80,0x3f80,0x3f6dbec4,0x3f6dbec4,0x3f80,0x3f80,0xbec4bf6d,0xbec4bf6d,0x3f80,0x3f80,0xbf6d3ec4,0xbf6d3ec4,
  0x3f808000,0x3f808000,0x3f6dbec4,0x3f6dbec4,0x3f808000,0x3f808000,0xbec4bf6d,0xbec4bf6d,0x3f808000,0x3f808000,0xbf6d3ec4,0xbf6d3ec4,
  0x3f808000,0x3f808000,0x3ec43f6d,0x3ec43f6d,0x3dc93f7f,0x3f7fbdc9,0x3ef13f62,0x3f62bef1,0x3ef13f62,0x3f62bef1,0x3f22bf46,0xbf46bf22,
  0x3f463f22,0x3f22bf46,0xbf75be95,0xbe953f75,0x3f753e95,0x3e95bf75,0x3dc93f7f,0x3f7fbdc9,0x3f7fbdc9,0xbdc9bf7f,0x3f62bef1,0xbef1bf62,
  0x3f62bef1,0xbef1bf62,0xbf46bf22,0xbf223f46,0x3f22bf46,0xbf46bf22,0xbe953f75,0x3f753e95,0x3e95bf75,0xbf75be95,0x3f7fbdc9,0xbdc9bf7f,
  0x3e483f7b,0xbe48bf7b,0x3f0e3f55,0xbf0ebf55,0x3f553f0e,0xbf55bf0e,0x3e48bf7b,0xbe483f7b,0x3f7bbe48,0xbf7b3e48,0xbf553f0e,0x3f55bf0e,
  0x3f0ebf55,0xbf0e3f55,0x3f7b3e48,0xbf7bbe48,0x3f7bbe48,0xbf7b3e48,0x3f55bf0e,0xbf553f0e,0x3f0ebf55,0xbf0e3f55,0xbf7bbe48,0x3f7b3e48,
  0xbe48bf7b,0x3e483f7b,0x3f0e3f55,0xbf0ebf55,0xbf55bf0e,0x3f553f0e,0x3e48bf7b,0xbe483f7b,0x3e953f75,0xbf753e95,0x3f223f46,0xbf463f22,
  0x3f7f3dc9,0xbdc93f7f,0xbe95bf75,0x3f75be95,0x3ef1bf62,0x3f623ef1,0xbdc93f7f,0xbf7fbdc9,0xbf22bf46,0x3f46bf22,0x3ef1bf62,0x3f623ef1,
  0x3f75be95,0x3e953f75,0x3f46bf22,0x3f223f46,0x3dc9bf7f,0x3f7f3dc9,0xbf753e95,0xbe95bf75,0xbf62bef1,0x3ef1bf62,0x3f7f3dc9,0xbdc93f7f,
  0xbf463f22,0xbf22bf46,0xbf62bef1,0x3ef1bf62,0x3f353f35,0x3f353f35,0x3f6d3ec4,0x3f6d3ec4,0xbf35bf35,0xbf35bf35,0xbec43f6d,0xbec43f6d,
  0x3f353f35,0x3f353f35,0xbf6dbec4,0xbf6dbec4,0xbf35bf35,0xbf35bf35,0x3ec4bf6d,0x3ec4bf6d,0x3f35bf35,0x3f35bf35,0x3ec4bf6d,0x3ec4bf6d,
  0xbf353f35,0xbf353f35,0x3f6d3ec4,0x3f6d3ec4,0x3f35bf35,0x3f35bf35,0xbec43f6d,0xbec43f6d,0xbf353f35,0xbf353f35,0xbf6dbec4,0xbf6dbec4,
  0x3f463f22,0x3f22bf46,0x3f753e95,0x3e95bf75,0xbf75be95,0xbe953f75,0x3dc93f7f,0x3f7fbdc9,0x3f7fbdc9,0xbdc9bf7f,0xbf623ef1,0x3ef13f62,
  0xbf623ef1,0x3ef13f62,0xbf46bf22,0xbf223f46,0x3f22bf46,0xbf46bf22,0x3e95bf75,0xbf75be95,0xbe953f75,0x3f753e95,0x3f7fbdc9,0xbdc9bf7f,
  0xbdc9bf7f,0xbf7f3dc9,0x3ef13f62,0x3f62bef1,0x3ef13f62,0x3f62bef1,0xbf223f46,0x3f463f22,0x3f553f0e,0xbf55bf0e,0x3f7b3e48,0xbf7bbe48,
  0xbf7b3e48,0x3f7bbe48,0x3f0e3f55,0xbf0ebf55,0x3f0ebf55,0xbf0e3f55,0xbe483f7b,0x3e48bf7b,0x3e483f7b,0xbe48bf7b,0xbf553f0e,0x3f55bf0e,
  0x3f0ebf55,0xbf0e3f55,0x3e48bf7b,0xbe483f7b,0x3e483f7b,0xbe48bf7b,0x3f55bf0e,0xbf553f0e,0xbf55bf0e,0x3f553f0e,0x3f7b3e48,0xbf7bbe48,
  0x3f7bbe48,0xbf7b3e48,0x3f0e3f55,0xbf0ebf55,0x3f623ef1,0xbef13f62,0x3f7f3dc9,0xbdc93f7f,0xbf463f22,0xbf22bf46,0x3f623ef1,0xbef13f62,
  0xbe95bf75,0x3f75be95,0x3f223f46,0xbf463f22,0x3f7f3dc9,0xbdc93f7f,0x3e953f75,0xbf753e95,0x3ef1bf62,0x3f623ef1,0x3dc9bf7f,0x3f7f3dc9,
  0x3f223f46,0xbf463f22,0x3ef1bf62,0x3f623ef1,0xbf753e95,0xbe95bf75,0x3f46bf22,0x3f223f46,0x3dc9bf7f,0x3f7f3dc9,0x3f75be95,0x3e953f75,
  0x3f80,0x3f80,0x3ec43f6d,0x3ec43f6d,0x3f80,0x3f80,0x3f6dbec4,0x3f6dbec4,0x3f80,0x3f80,0xbec4bf6d,0xbec4bf6d,
  0x3f80,0x3f80,0xbf6d3ec4,0xbf6d3ec4,0x3f808000,0x3f808000,0x3f6dbec4,0x3f6dbec4,0x3f808000,0x3f808000,0xbec4bf6d,0xbec4bf6d,
  0x3f808000,0x3f808000,0xbf6d3ec4,0xbf6d3ec4,0x3f808000,0x3f808000,0x3ec43f6d,0x3ec43f6d,0xbdc9bf7f,0xbf7f3dc9,0xbef1bf62,0xbf623ef1,
  0xbef1bf62,0xbf623ef1,0xbf223f46,0x3f463f22,0xbf46bf22,0xbf223f46,0x3f753e95,0x3e95bf75,0xbf75be95,0xbe953f75,0xbdc9bf7f,0xbf7f3dc9,
  0xbf7f3dc9,0x3dc93f7f,0xbf623ef1,0x3ef13f62,0xbf623ef1,0x3ef13f62,0x3f463f22,0x3f22bf46,0xbf223f46,0x3f463f22,0x3e95bf75,0xbf75be95,
  0xbe953f75,0x3f753e95,0xbf7f3dc9,0x3dc93f7f,0x3e483f7b,0xbe48bf7b,0x3f0e3f55,0xbf0ebf55,0x3f553f0e,0xbf55bf0e,0x3e48bf7b,0xbe483f7b,
  0x3f7bbe48,0xbf7b3e48,0xbf553f0e,0x3f55bf0e,0x3f0ebf55,0xbf0e3f55,0x3f7b3e48,0xbf7bbe48,0x3f7bbe48,0xbf7b3e48,0x3f55bf0e,0xbf553f0e,
  0x3f0ebf55,0xbf0e3f55,0xbf7bbe48,0x3f7b3e48,0xbe48bf7b,0x3e483f7b,0x3f0e3f55,0xbf0ebf55,0xbf55bf0e,0x3f553f0e,0x3e48bf7b,0xbe483f7b,
  0xbe95bf75,0x3f75be95,0xbf22bf46,0x3f46bf22,0xbf7fbdc9,0x3dc9bf7f,0x3e953f75,0xbf753e95,0xbef13f62,0xbf62bef1,0x3dc9bf7f,0x3f7f3dc9,
  0x3f223f46,0xbf463f22,0xbef13f62,0xbf62bef1,0xbf753e95,0xbe95bf75,0xbf463f22,0xbf22bf46,0xbdc93f7f,0xbf7fbdc9,0x3f75be95,0x3e953f75,
  0x3f623ef1,0xbef13f62,0xbf7fbdc9,0x3dc9bf7f,0x3f46bf22,0x3f223f46,0x3f623ef1,0xbef13f62,0x3f353f35,0x3f353f35,0x3f6d3ec4,0x3f6d3ec4,
  0xbf35bf35,0xbf35bf35,0xbec43f6d,0xbec43f6d,0x3f353f35,0x3f353f35,0xbf6dbec4,0xbf6dbec4,0xbf35bf35,0xbf35bf35,0x3ec4bf6d,0x3ec4bf6d,
  0x3f35bf35,0x3f35bf35,0x3ec4bf6d,0x3ec4bf6d,0xbf353f35,0xbf353f35,0x3f6d3ec4,0x3f6d3ec4,0x3f35bf35,0x3f35bf35,0xbec43f6d,0xbec43f6d,
  0xbf353f35,0xbf353f35,0xbf6dbec4,0xbf6dbec4,0xbf46bf22,0xbf223f46,0xbf75be95,0xbe953f75,0x3f753e95,0x3e95bf75,0xbdc9bf7f,0xbf7f3dc9,
  0xbf7f3dc9,0x3dc93f7f,0x3f62bef1,0xbef1bf62,0x3f62bef1,0xbef1bf62,0x3f463f22,0x3f22bf46,0xbf223f46,0x3f463f22,0xbe953f75,0x3f753e95,
  0x3e95bf75,0xbf75be95,0xbf7f3dc9,0x3dc93f7f,0x3dc93f7f,0x3f7fbdc9,0xbef1bf62,0xbf623ef1,0xbef1bf62,0xbf623ef1,0x3f22bf46,0xbf46bf22,
  0x3f553f0e,0xbf55bf0e,0x3f7b3e48,0xbf7bbe48,0xbf7b3e48,0x3f7bbe48,0x3f0e3f55,0xbf0ebf55,0x3f0ebf55,0xbf0e3f55,0xbe483f7b,0x3e48bf7b,
  0x3e483f7b,0xbe48bf7b,0xbf553f0e,0x3f55bf0e,0x3f0ebf55,0xbf0e3f55,0x3e48bf7b,0xbe483f7b,0x3e483f7b,0xbe48bf7b,0x3f55bf0e,0xbf553f0e,
  0xbf55bf0e,0x3f553f0e,0x3f7b3e48,0xbf7bbe48,0x3f7bbe48,0xbf7b3e48,0x3f0e3f55,0xbf0ebf55,0xbf62bef1,0x3ef1bf62,0xbf7fbdc9,0x3dc9bf7f,
  0x3f46bf22,0x3f223f46,0xbf62bef1,0x3ef1bf62,0x3e953f75,0xbf753e95,0xbf22bf46,0x3f46bf22,0xbf7fbdc9,0x3dc9bf7f,0xbe95bf75,0x3f75be95,
  0xbef13f62,0xbf62bef1,0xbdc93f7f,0xbf7fbdc9,0xbf22bf46,0x3f46bf22,0xbef13f62,0xbf62bef1,0x3f75be95,0x3e953f75,0xbf463f22,0xbf22bf46,
  0xbdc93f7f,0xbf7fbdc9,0xbf753e95,0xbe95bf75,0x3f80,0x3f80,0x3f0e3f55,0x3f0e3f55,0x3f80,0x3f80,0x3f55bf0e,0x3f55bf0e,
  0x3f80,0x3f80,0xbf0ebf55,0xbf0ebf55,0x3f80,0x3f80,0xbf553f0e,0xbf553f0e,0x3f808000,0x3f808000,0x3f55bf0e,0x3f55bf0e,
  0x3f808000,0x3f808000,0xbf0ebf55,0xbf0ebf55,0x3f808000,0x3f808000,0xbf553f0e,0xbf553f0e,0x3f808000,0x3f808000,0x3f0e3f55,0x3f0e3f55,
  0x3e163f7d,0x3f7dbe16,0x3f2c3f3e,0x3f3ebf2c,0x3f043f5c,0x3f5cbf04,0x3edbbf67,0xbf67bedb,0x3f4e3f18,0x3f18bf4e,0xbf80bd49,0xbd493f80,
  0x3f783e79,0x3e79bf78,0x3eac3f71,0x3f71beac,0x3f7dbe16,0xbe16bf7d,0x3f3ebf2c,0xbf2cbf3e,0x3f5cbf04,0xbf04bf5c,0xbf67bedb,0xbedb3f67,
  0x3f18bf4e,0xbf4ebf18,0xbd493f80,0x3f803d49,0x3e79bf78,0xbf78be79,0x3f71beac,0xbeacbf71,0x3e953f75,0xbe95bf75,0x3f463f22,0xbf46bf22,
  0x3f623ef1,0xbf62bef1,0xbdc9bf7f,0x3dc93f7f,0x3f75be95,0xbf753e95,0xbf223f46,0x3f22bf46,0x3ef1bf62,0xbef13f62,0x3f7fbdc9,0xbf7f3dc9,
  0x3f75be95,0xbf753e95,0x3f22bf46,0xbf223f46,0x3ef1bf62,0xbef13f62,0xbf7f3dc9,0x3f7fbdc9,0xbe95bf75,0x3e953f75,0x3f463f22,0xbf46bf22,
  0xbf62bef1,0x3f623ef1,0xbdc9bf7f,0x3dc93f7f,0x3edb3f67,0xbf673edb,0x3f5c3f04,0xbf043f5c,0x3f80bd49,0x3d493f80,0xbf18bf4e,0x3f4ebf18,
  0x3eacbf71,0x3f713eac,0x3e793f78,0xbf783e79,0xbf3ebf2c,0x3f2cbf3e,0x3e16bf7d,0x3f7d3e16,0x3f67bedb,0x3edb3f67,0x3f04bf5c,0x3f5c3f04,
  0xbd49bf80,0x3f80bd49,0xbf4e3f18,0xbf18bf4e,0xbf71beac,0x3eacbf71,0x3f78be79,0x3e793f78,0xbf2c3f3e,0xbf3ebf2c,0xbf7dbe16,0x3e16bf7d,
  0x3f6d3ec4,0x3f6d3ec4,0x3f7bbe48,0x3f7bbe48,0xbf6dbec4,0xbf6dbec4,0x3e483f7b,0x3e483f7b,0x3f6d3ec4,0x3f6d3ec4,0xbf7b3e48,0xbf7b3e48,
  0xbf6dbec4,0xbf6dbec4,0xbe48bf7b,0xbe48bf7b,0x3ec4bf6d,0x3ec4bf6d,0xbe48bf7b,0xbe48bf7b,0xbec43f6d,0xbec43f6d,0x3f7bbe48,0x3f7bbe48,
  0x3ec4bf6d,0x3ec4bf6d,0x3e483f7b,0x3e483f7b,0xbec43f6d,0xbec43f6d,0xbf7b3e48,0xbf7b3e48,0x3f783e79,0x3e79bf78,0x3f71beac,0xbeacbf71,
  0xbf7d3e16,0x3e163f7d,0x3f2c3f3e,0x3f3ebf2c,0x3f5cbf04,0xbf04bf5c,0xbedb3f67,0x3f673edb,0xbf183f4e,0x3f4e3f18,0xbf80bd49,0xbd493f80,
  0x3e79bf78,0xbf78be79,0xbeacbf71,0xbf713eac,0x3e163f7d,0x3f7dbe16,0x3f3ebf2c,0xbf2cbf3e,0xbf04bf5c,0xbf5c3f04,0x3f673edb,0x3edbbf67,
  0x3f4e3f18,0x3f18bf4e,0xbd493f80,0x3f803d49,0x3f7f3dc9,0xbf7fbdc9,0x3f62bef1,0xbf623ef1,0xbf463f22,0x3f46bf22,0x3f753e95,0xbf75be95,
  0x3dc9bf7f,0xbdc93f7f,0x3ef13f62,0xbef1bf62,0x3f223f46,0xbf22bf46,0xbe953f75,0x3e95bf75,0x3dc9bf7f,0xbdc93f7f,0xbef1bf62,0x3ef13f62,
  0x3f223f46,0xbf22bf46,0x3e95bf75,0xbe953f75,0xbf7fbdc9,0x3f7f3dc9,0x3f62bef1,0xbf623ef1,0x3f46bf22,0xbf463f22,0x3f753e95,0xbf75be95,
  0x3f80bd49,0x3d493f80,0x3f4ebf18,0x3f183f4e,0xbeac3f71,0xbf71beac,0x3f78be79,0x3e793f78,0xbf3ebf2c,0x3f2cbf3e,0x3f7d3e16,0xbe163f7d,
  0x3f67bedb,0x3edb3f67,0x3f5c3f04,0xbf043f5c,0xbd49bf80,0x3f80bd49,0xbf18bf4e,0x3f4ebf18,0x3f713eac,0xbeac3f71,0xbe79bf78,0x3f78be79,
  0xbf2c3f3e,0xbf3ebf2c,0x3e16bf7d,0x3f7d3e16,0xbedbbf67,0x3f67bedb,0x3f04bf5c,0x3f5c3f04,0x3f80,0x3f80,0x3f0e3f55,0x3f0e3f55,
  0x3f80,0x3f80,0x3f55bf0e,0x3f55bf0e,0x3f80,0x3f80,0xbf0ebf55,0xbf0ebf55,0x3f80,0x3f80,0xbf553f0e,0xbf553f0e,
  0x3f808000,0x3f808000,0x3f55bf0e,0x3f55bf0e,0x3f808000,0x3f808000,0xbf0ebf55,0xbf0ebf55,0x3f808000,0x3f808000,0xbf553f0e,0xbf553f0e,
  0x3f808000,0x3f808000,0x3f0e3f55,0x3f0e3f55,0xbe16bf7d,0xbf7d3e16,0xbf2cbf3e,0xbf3e3f2c,0xbf04bf5c,0xbf5c3f04,0xbedb3f67,0x3f673edb,
  0xbf4ebf18,0xbf183f4e,0x3f803d49,0x3d49bf80,0xbf78be79,0xbe793f78,0xbeacbf71,0xbf713eac,0xbf7d3e16,0x3e163f7d,0xbf3e3f2c,0x3f2c3f3e,
  0xbf5c3f04,0x3f043f5c,0x3f673edb,0x3edbbf67,0xbf183f4e,0x3f4e3f18,0x3d49bf80,0xbf80bd49,0xbe793f78,0x3f783e79,0xbf713eac,0x3eac3f71,
  0x3e953f75,0xbe95bf75,0x3f463f22,0xbf46bf22,0x3f623ef1,0xbf62bef1,0xbdc9bf7f,0x3dc93f7f,0x3f75be95,0xbf753e95,0xbf223f46,0x3f22bf46,
  0x3ef1bf62,0xbef13f62,0x3f7fbdc9,0xbf7f3dc9,0x3f75be95,0xbf753e95,0x3f22bf46,0xbf223f46,0x3ef1bf62,0xbef13f62,0xbf7f3dc9,0x3f7fbdc9,
  0xbe95bf75,0x3e953f75,0x3f463f22,0xbf46bf22,0xbf62bef1,0x3f623ef1,0xbdc9bf7f,0x3dc93f7f,0xbedbbf67,0x3f67bedb,0xbf5cbf04,0x3f04bf5c,
  0xbf803d49,0xbd49bf80,0x3f183f4e,0xbf4e3f18,0xbeac3f71,0xbf71beac,0xbe79bf78,0x3f78be79,0x3f3e3f2c,0xbf2c3f3e,0xbe163f7d,0xbf7dbe16,
  0xbf673edb,0xbedbbf67,0xbf043f5c,0xbf5cbf04,0x3d493f80,0xbf803d49,0x3f4ebf18,0x3f183f4e,0x3f713eac,0xbeac3f71,0xbf783e79,0xbe79bf78,
  0x3f2cbf3e,0x3f3e3f2c,0x3f7d3e16,0xbe163f7d,0x3f6d3ec4,0x3f6d3ec4,0x3f7bbe48,0x3f7bbe48,0xbf6dbec4,0xbf6dbec4,0x3e483f7b,0x3e483f7b,
  0x3f6d3ec4,0x3f6d3ec4,0xbf7b3e48,0xbf7b3e48,0xbf6dbec4,0xbf6dbec4,0xbe48bf7b,0xbe48bf7b,0x3ec4bf6d,0x3ec4bf6d,0xbe48bf7b,0xbe48bf7b,
  0xbec43f6d,0xbec43f6d,0x3f7bbe48,0x3f7bbe48,0x3ec4bf6d,0x3ec4bf6d,0x3e483f7b,0x3e483f7b,0xbec43f6d,0xbec43f6d,0xbf7b3e48,0xbf7b3e48,
  0xbf78be79,0xbe793f78,0xbf713eac,0x3eac3f71,0x3f7dbe16,0xbe16bf7d,0xbf2cbf3e,0xbf3e3f2c,0xbf5c3f04,0x3f043f5c,0x3edbbf67,0xbf67bedb,
  0x3f18bf4e,0xbf4ebf18,0x3f803d49,0x3d49bf80,0xbe793f78,0x3f783e79,0x3eac3f71,0x3f71beac,0xbe16bf7d,0xbf7d3e16,0xbf3e3f2c,0x3f2c3f3e,
  0x3f043f5c,0x3f5cbf04,0xbf67bedb,0xbedb3f67,0xbf4ebf18,0xbf183f4e,0x3d49bf80,0xbf80bd49,0x3f7f3dc9,0xbf7fbdc9,0x3f62bef1,0xbf623ef1,
  0xbf463f22,0x3f46bf22,0x3f753e95,0xbf75be95,0x3dc9bf7f,0xbdc93f7f,0x3ef13f62,0xbef1bf62,0x3f223f46,0xbf22bf46,0xbe953f75,0x3e95bf75,
  0x3dc9bf7f,0xbdc93f7f,0xbef1bf62,0x3ef13f62,0x3f223f46,0xbf22bf46,0x3e95bf75,0xbe953f75,0xbf7fbdc9,0x3f7f3dc9,0x3f62bef1,0xbf623ef1,
  0x3f46bf22,0xbf463f22,0x3f753e95,0xbf75be95,0xbf803d49,0xbd49bf80,0xbf4e3f18,0xbf18bf4e,0x3eacbf71,0x3f713eac,0xbf783e79,0xbe79bf78,
  0x3f3e3f2c,0xbf2c3f3e,0xbf7dbe16,0x3e16bf7d,0xbf673edb,0xbedbbf67,0xbf5cbf04,0x3f04bf5c,0x3d493f80,0xbf803d49,0x3f183f4e,0xbf4e3f18,
  0xbf71beac,0x3eacbf71,0x3e793f78,0xbf783e79,0x3f2cbf3e,0x3f3e3f2c,0xbe163f7d,0xbf7dbe16,0x3edb3f67,0xbf673edb,0xbf043f5c,0xbf5cbf04,
  0x3f80,0x3f80,0x3f353f35,0x3f353f35,0x3f80,0x3f80,0x3f35bf35,0x3f35bf35,0x3f80,0x3f80,0xbf35bf35,0xbf35bf35,
  0x3f80,0x3f80,0xbf353f35,0xbf353f35,0x3f808000,0x3f808000,0x3f35bf35,0x3f35bf35,0x3f808000,0x3f808000,0xbf35bf35,0xbf35bf35,
  0x3f808000,0x3f808000,0xbf353f35,0xbf353f35,0x3f808000,0x3f808000,0x3f353f35,0x3f353f35,0x3e483f7b,0x3f7bbe48,0x3f553f0e,0x3f0ebf55,
  0x3f0e3f55,0x3f55bf0e,0x3e48bf7b,0xbf7bbe48,0x3f553f0e,0x3f0ebf55,0xbf7b3e48,0x3e483f7b,0x3f7b3e48,0x3e48bf7b,0x3f0e3f55,0x3f55bf0e,
  0x3f7bbe48,0xbe48bf7b,0x3f0ebf55,0xbf55bf0e,0x3f55bf0e,0xbf0ebf55,0xbf7bbe48,0xbe483f7b,0x3f0ebf55,0xbf55bf0e,0x3e483f7b,0x3f7bbe48,
  0x3e48bf7b,0xbf7bbe48,0x3f55bf0e,0xbf0ebf55,0x3ec43f6d,0xbec4bf6d,0x3f6d3ec4,0xbf6dbec4,0x3f6d3ec4,0xbf6dbec4,0xbec4bf6d,0x3ec43f6d,
  0x3f6dbec4,0xbf6d3ec4,0xbec43f6d,0x3ec4bf6d,0x3ec4bf6d,0xbec43f6d,0x3f6dbec4,0xbf6d3ec4,0x3f6dbec4,0xbf6d3ec4,0x3ec4bf6d,0xbec43f6d,
  0x3ec4bf6d,0xbec43f6d,0xbf6d3ec4,0x3f6dbec4,0xbec4bf6d,0x3ec43f6d,0x3f6d3ec4,0xbf6dbec4,0xbf6dbec4,0x3f6d3ec4,0xbec4bf6d,0x3ec43f6d,
  0x3f0e3f55,0xbf553f0e,0x3f7b3e48,0xbe483f7b,0x3f7bbe48,0x3e483f7b,0xbf55bf0e,0x3f0ebf55,0x3e48bf7b,0x3f7b3e48,0x3f0e3f55,0xbf553f0e,
  0xbf55bf0e,0x3f0ebf55,0xbe48bf7b,0x3f7bbe48,0x3f55bf0e,0x3f0e3f55,0x3e48bf7b,0x3f7b3e48,0xbe48bf7b,0x3f7bbe48,0xbf0e3f55,0xbf55bf0e,
  0xbf7bbe48,0x3e48bf7b,0x3f55bf0e,0x3f0e3f55,0xbf0e3f55,0xbf55bf0e,0xbf7b3e48,0xbe48bf7b,0x3f800000,0x3f800000,0x3f35bf35,0x3f35bf35,
  0xbf800000,0xbf800000,0x3f353f35,0x3f353f35,0x3f800000,0x3f800000,0xbf353f35,0xbf353f35,0xbf800000,0xbf800000,0xbf35bf35,0xbf35bf35,
  0xbf80,0xbf80,0xbf35bf35,0xbf35bf35,0x3f80,0x3f80,0x3f35bf35,0x3f35bf35,0xbf80,0xbf80,0x3f353f35,0x3f353f35,
  0x3f80,0x3f80,0xbf353f35,0xbf353f35,0x3f7bbe48,0xbe48bf7b,0x3f0ebf55,0xbf55bf0e,0xbf553f0e,0x3f0e3f55,0x3f7b3e48,0x3e48bf7b,
  0x3f0ebf55,0xbf55bf0e,0x3e483f7b,0x3f7bbe48,0xbe483f7b,0x3f7b3e48,0xbf553f0e,0x3f0e3f55,0xbe48bf7b,0xbf7b3e48,0xbf55bf0e,0xbf0e3f55,
  0x3f0e3f55,0x3f55bf0e,0x3e48bf7b,0xbf7bbe48,0xbf55bf0e,0xbf0e3f55,0x3f7bbe48,0xbe48bf7b,0x3f7b3e48,0x3e48bf7b,0x3f0e3f55,0x3f55bf0e,
  0x3f6dbec4,0xbf6d3ec4,0x3ec4bf6d,0xbec43f6d,0xbec43f6d,0x3ec4bf6d,0x3f6dbec4,0xbf6d3ec4,0xbec4bf6d,0x3ec43f6d,0x3f6d3ec4,0xbf6dbec4,
  0x3f6d3ec4,0xbf6dbec4,0x3ec43f6d,0xbec4bf6d,0xbec4bf6d,0x3ec43f6d,0xbf6dbec4,0x3f6d3ec4,0x3f6d3ec4,0xbf6dbec4,0xbec4bf6d,0x3ec43f6d,
  0xbf6d3ec4,0x3f6dbec4,0x3ec4bf6d,0xbec43f6d,0x3ec4bf6d,0xbec43f6d,0x3f6dbec4,0xbf6d3ec4,0x3f55bf0e,0x3f0e3f55,0x3e48bf7b,0x3f7b3e48,
  0x3e483f7b,0xbf7b3e48,0x3f0ebf55,0x3f553f0e,0xbf7bbe48,0x3e48bf7b,0x3f55bf0e,0x3f0e3f55,0x3f0ebf55,0x3f553f0e,0x3f7bbe48,0x3e483f7b,
  0xbf0ebf55,0x3f55bf0e,0xbf7bbe48,0x3e48bf7b,0x3f7bbe48,0x3e483f7b,0xbf55bf0e,0x3f0ebf55,0xbe483f7b,0xbf7bbe48,0xbf0ebf55,0x3f55bf0e,
  0xbf55bf0e,0x3f0ebf55,0xbe48bf7b,0x3f7bbe48,0x3f80,0x3f80,0x3f353f35,0x3f353f35,0x3f80,0x3f80,0x3f35bf35,0x3f35bf35,
  0x3f80,0x3f80,0xbf35bf35,0xbf35bf35,0x3f80,0x3f80,0xbf353f35,0xbf353f35,0x3f808000,0x3f808000,0x3f35bf35,0x3f35bf35,
  0x3f808000,0x3f808000,0xbf35bf35,0xbf35bf35,0x3f808000,0x3f808000,0xbf353f35,0xbf353f35,0x3f808000,0x3f808000,0x3f353f35,0x3f353f35,
  0xbe48bf7b,0xbf7b3e48,0xbf55bf0e,0xbf0e3f55,0xbf0ebf55,0xbf553f0e,0xbe483f7b,0x3f7b3e48,0xbf55bf0e,0xbf0e3f55,0x3f7bbe48,0xbe48bf7b,
  0xbf7bbe48,0xbe483f7b,0xbf0ebf55,0xbf553f0e,0xbf7b3e48,0x3e483f7b,0xbf0e3f55,0x3f553f0e,0xbf553f0e,0x3f0e3f55,0x3f7b3e48,0x3e48bf7b,
  0xbf0e3f55,0x3f553f0e,0xbe48bf7b,0xbf7b3e48,0xbe483f7b,0x3f7b3e48,0xbf553f0e,0x3f0e3f55,0x3ec43f6d,0xbec4bf6d,0x3f6d3ec4,0xbf6dbec4,
  0x3f6d3ec4,0xbf6dbec4,0xbec4bf6d,0x3ec43f6d,0x3f6dbec4,0xbf6d3ec4,0xbec43f6d,0x3ec4bf6d,0x3ec4bf6d,0xbec43f6d,0x3f6dbec4,0xbf6d3ec4,
  0x3f6dbec4,0xbf6d3ec4,0x3ec4bf6d,0xbec43f6d,0x3ec4bf6d,0xbec43f6d,0xbf6d3ec4,0x3f6dbec4,0xbec4bf6d,0x3ec43f6d,0x3f6d3ec4,0xbf6dbec4,
  0xbf6dbec4,0x3f6d3ec4,0xbec4bf6d,0x3ec43f6d,0xbf0ebf55,0x3f55bf0e,0xbf7bbe48,0x3e48bf7b,0xbf7b3e48,0xbe48bf7b,0x3f553f0e,0xbf0e3f55,
  0xbe483f7b,0xbf7bbe48,0xbf0ebf55,0x3f55bf0e,0x3f553f0e,0xbf0e3f55,0x3e483f7b,0xbf7b3e48,0xbf553f0e,0xbf0ebf55,0xbe483f7b,0xbf7bbe48,
  0x3e483f7b,0xbf7b3e48,0x3f0ebf55,0x3f553f0e,0x3f7b3e48,0xbe483f7b,0xbf553f0e,0xbf0ebf55,0x3f0ebf55,0x3f553f0e,0x3f7bbe48,0x3e483f7b,
  0x3f800000,0x3f800000,0x3f35bf35,0x3f35bf35,0xbf800000,0xbf800000,0x3f353f35,0x3f353f35,0x3f800000,0x3f800000,0xbf353f35,0xbf353f35,
  0xbf800000,0xbf800000,0xbf35bf35,0xbf35bf35,0xbf80,0xbf80,0xbf35bf35,0xbf35bf35,0x3f80,0x3f80,0x3f35bf35,0x3f35bf35,
  0xbf80,0xbf80,0x3f353f35,0x3f353f35,0x3f80,0x3f80,0xbf353f35,0xbf353f35,0xbf7b3e48,0x3e483f7b,0xbf0e3f55,0x3f553f0e,
  0x3f55bf0e,0xbf0ebf55,0xbf7bbe48,0xbe483f7b,0xbf0e3f55,0x3f553f0e,0xbe48bf7b,0xbf7b3e48,0x3e48bf7b,0xbf7bbe48,0x3f55bf0e,0xbf0ebf55,
  0x3e483f7b,0x3f7bbe48,0x3f553f0e,0x3f0ebf55,0xbf0ebf55,0xbf553f0e,0xbe483f7b,0x3f7b3e48,0x3f553f0e,0x3f0ebf55,0xbf7b3e48,0x3e483f7b,
  0xbf7bbe48,0xbe483f7b,0xbf0ebf55,0xbf553f0e,0x3f6dbec4,0xbf6d3ec4,0x3ec4bf6d,0xbec43f6d,0xbec43f6d,0x3ec4bf6d,0x3f6dbec4,0xbf6d3ec4,
  0xbec4bf6d,0x3ec43f6d,0x3f6d3ec4,0xbf6dbec4,0x3f6d3ec4,0xbf6dbec4,0x3ec43f6d,0xbec4bf6d,0xbec4bf6d,0x3ec43f6d,0xbf6dbec4,0x3f6d3ec4,
  0x3f6d3ec4,0xbf6dbec4,0xbec4bf6d,0x3ec43f6d,0xbf6d3ec4,0x3f6dbec4,0x3ec4bf6d,0xbec43f6d,0x3ec4bf6d,0xbec43f6d,0x3f6dbec4,0xbf6d3ec4,
  0xbf553f0e,0xbf0ebf55,0xbe483f7b,0xbf7bbe48,0xbe48bf7b,0x3f7bbe48,0xbf0e3f55,0xbf55bf0e,0x3f7b3e48,0xbe483f7b,0xbf553f0e,0xbf0ebf55,
  0xbf0e3f55,0xbf55bf0e,0xbf7b3e48,0xbe48bf7b,0x3f0e3f55,0xbf553f0e,0x3f7b3e48,0xbe483f7b,0xbf7b3e48,0xbe48bf7b,0x3f553f0e,0xbf0e3f55,
  0x3e48bf7b,0x3f7b3e48,0x3f0e3f55,0xbf553f0e,0x3f553f0e,0xbf0e3f55,0x3e483f7b,0xbf7b3e48,0x3f80,0x3f80,0x3f553f0e,0x3f553f0e,
  0x3f80,0x3f80,0x3f0ebf55,0x3f0ebf55,0x3f80,0x3f80,0xbf55bf0e,0xbf55bf0e,0x3f80,0x3f80,0xbf0e3f55,0xbf0e3f55,
  0x3f808000,0x3f808000,0x3f0ebf55,0x3f0ebf55,0x3f808000,0x3f808000,0xbf55bf0e,0xbf55bf0e,0x3f808000,0x3f808000,0xbf0e3f55,0xbf0e3f55,
  0x3f808000,0x3f808000,0x3f553f0e,0x3f553f0e,0x3e793f78,0x3f78be79,0x3f713eac,0x3eacbf71,0x3f183f4e,0x3f4ebf18,0xbd49bf80,0xbf803d49,
  0x3f5c3f04,0x3f04bf5c,0xbf673edb,0x3edb3f67,0x3f7d3e16,0x3e16bf7d,0x3f3e3f2c,0x3f2cbf3e,0x3f78be79,0xbe79bf78,0x3eacbf71,0xbf71beac,
  0x3f4ebf18,0xbf18bf4e,0xbf803d49,0x3d493f80,0x3f04bf5c,0xbf5cbf04,0x3edb3f67,0x3f67bedb,0x3e16bf7d,0xbf7dbe16,0x3f2cbf3e,0xbf3ebf2c,
  0x3ef13f62,0xbef1bf62,0x3f7f3dc9,0xbf7fbdc9,0x3f753e95,0xbf75be95,0xbf22bf46,0x3f223f46,0x3f62bef1,0xbf623ef1,0xbdc93f7f,0x3dc9bf7f,
  0x3e95bf75,0xbe953f75,0x3f46bf22,0xbf463f22,0x3f62bef1,0xbf623ef1,0x3dc9bf7f,0xbdc93f7f,0x3e95bf75,0xbe953f75,0xbf463f22,0x3f46bf22,
  0xbef1bf62,0x3ef13f62,0x3f7f3dc9,0xbf7fbdc9,0xbf75be95,0x3f753e95,0xbf22bf46,0x3f223f46,0x3f2c3f3e,0xbf3e3f2c,0x3f7dbe16,0x3e163f7d,
  0x3f71beac,0x3eac3f71,0xbf78be79,0x3e79bf78,0x3d49bf80,0x3f803d49,0x3f4e3f18,0xbf183f4e,0xbf67bedb,0x3edbbf67,0xbf04bf5c,0x3f5cbf04,
  0x3f3ebf2c,0x3f2c3f3e,0xbe16bf7d,0x3f7dbe16,0xbeacbf71,0x3f71beac,0xbe793f78,0xbf78be79,0xbf80bd49,0x3d49bf80,0x3f18bf4e,0x3f4e3f18,
  0xbedb3f67,0xbf67bedb,0xbf5c3f04,0xbf04bf5c,0x3f6dbec4,0x3f6dbec4,0x3e48bf7b,0x3e48bf7b,0xbf6d3ec4,0xbf6d3ec4,0x3f7b3e48,0x3f7b3e48,
  0x3f6dbec4,0x3f6dbec4,0xbe483f7b,0xbe483f7b,0xbf6d3ec4,0xbf6d3ec4,0xbf7bbe48,0xbf7bbe48,0xbec4bf6d,0xbec4bf6d,0xbf7bbe48,0xbf7bbe48,
  0x3ec43f6d,0x3ec43f6d,0x3e48bf7b,0x3e48bf7b,0xbec4bf6d,0xbec4bf6d,0x3f7b3e48,0x3f7b3e48,0x3ec43f6d,0x3ec43f6d,0xbe483f7b,0xbe483f7b,
  0x3f4ebf18,0xbf18bf4e,0xbd49bf80,0xbf803d49,0xbf043f5c,0x3f5c3f04,0x3f67bedb,0xbedbbf67,0x3e16bf7d,0xbf7dbe16,0x3f3e3f2c,0x3f2cbf3e,
  0x3e793f78,0x3f78be79,0xbeac3f71,0x3f713eac,0xbf18bf4e,0xbf4e3f18,0xbf803d49,0x3d493f80,0x3f5c3f04,0x3f04bf5c,0xbedbbf67,0xbf673edb,
  0xbf7dbe16,0xbe163f7d,0x3f2cbf3e,0xbf3ebf2c,0x3f78be79,0xbe79bf78,0x3f713eac,0x3eacbf71,0x3f22bf46,0xbf223f46,0xbe95bf75,0x3e953f75,
  0x3dc93f7f,0xbdc9bf7f,0x3ef1bf62,0xbef13f62,0xbf46bf22,0x3f463f22,0x3f75be95,0xbf753e95,0x3f7fbdc9,0xbf7f3dc9,0x3f623ef1,0xbf62bef1,
  0xbf46bf22,0x3f463f22,0xbf753e95,0x3f75be95,0x3f7fbdc9,0xbf7f3dc9,0xbf62bef1,0x3f623ef1,0xbf223f46,0x3f22bf46,0xbe95bf75,0x3e953f75,
  0xbdc9bf7f,0x3dc93f7f,0x3ef1bf62,0xbef13f62,0x3edbbf67,0x3f673edb,0xbf04bf5c,0x3f5cbf04,0x3f2c3f3e,0xbf3e3f2c,0xbe16bf7d,0x3f7dbe16,
  0xbf713eac,0xbeacbf71,0x3e79bf78,0x3f783e79,0x3d49bf80,0x3f803d49,0x3f18bf4e,0x3f4e3f18,0xbf67bedb,0x3edbbf67,0xbf5c3f04,0xbf04bf5c,
  0x3f3ebf2c,0x3f2c3f3e,0xbf7d3e16,0xbe16bf7d,0x3eac3f71,0xbf713eac,0xbf78be79,0x3e79bf78,0xbf80bd49,0x3d49bf80,0xbf4ebf18,0x3f18bf4e,
  0x3f80,0x3f80,0x3f553f0e,0x3f553f0e,0x3f80,0x3f80,0x3f0ebf55,0x3f0ebf55,0x3f80,0x3f80,0xbf55bf0e,0xbf55bf0e,
  0x3f80,0x3f80,0xbf0e3f55,0xbf0e3f55,0x3f808000,0x3f808000,0x3f0ebf55,0x3f0ebf55,0x3f808000,0x3f808000,0xbf55bf0e,0xbf55bf0e,
  0x3f808000,0x3f808000,0xbf0e3f55,0xbf0e3f55,0x3f808000,0x3f808000,0x3f553f0e,0x3f553f0e,0xbe79bf78,0xbf783e79,0xbf71beac,0xbeac3f71,
  0xbf18bf4e,0xbf4e3f18,0x3d493f80,0x3f80bd49,0xbf5cbf04,0xbf043f5c,0x3f67bedb,0xbedbbf67,0xbf7dbe16,0xbe163f7d,0xbf3ebf2c,0xbf2c3f3e,
  0xbf783e79,0x3e793f78,0xbeac3f71,0x3f713eac,0xbf4e3f18,0x3f183f4e,0x3f80bd49,0xbd49bf80,0xbf043f5c,0x3f5c3f04,0xbedbbf67,0xbf673edb,
  0xbe163f7d,0x3f7d3e16,0xbf2c3f3e,0x3f3e3f2c,0x3ef13f62,0xbef1bf62,0x3f7f3dc9,0xbf7fbdc9,0x3f753e95,0xbf75be95,0xbf22bf46,0x3f223f46,
  0x3f62bef1,0xbf623ef1,0xbdc93f7f,0x3dc9bf7f,0x3e95bf75,0xbe953f75,0x3f46bf22,0xbf463f22,0x3f62bef1,0xbf623ef1,0x3dc9bf7f,0xbdc93f7f,
  0x3e95bf75,0xbe953f75,0xbf463f22,0x3f46bf22,0xbef1bf62,0x3ef13f62,0x3f7f3dc9,0xbf7fbdc9,0xbf75be95,0x3f753e95,0xbf22bf46,0x3f223f46,
  0xbf2cbf3e,0x3f3ebf2c,0xbf7d3e16,0xbe16bf7d,0xbf713eac,0xbeacbf71,0x3f783e79,0xbe793f78,0xbd493f80,0xbf80bd49,0xbf4ebf18,0x3f18bf4e,
  0x3f673edb,0xbedb3f67,0x3f043f5c,0xbf5c3f04,0xbf3e3f2c,0xbf2cbf3e,0x3e163f7d,0xbf7d3e16,0x3eac3f71,0xbf713eac,0x3e79bf78,0x3f783e79,
  0x3f803d49,0xbd493f80,0xbf183f4e,0xbf4ebf18,0x3edbbf67,0x3f673edb,0x3f5cbf04,0x3f043f5c,0x3f6dbec4,0x3f6dbec4,0x3e48bf7b,0x3e48bf7b,
  0xbf6d3ec4,0xbf6d3ec4,0x3f7b3e48,0x3f7b3e48,0x3f6dbec4,0x3f6dbec4,0xbe483f7b,0xbe483f7b,0xbf6d3ec4,0xbf6d3ec4,0xbf7bbe48,0xbf7bbe48,
  0xbec4bf6d,0xbec4bf6d,0xbf7bbe48,0xbf7bbe48,0x3ec43f6d,0x3ec43f6d,0x3e48bf7b,0x3e48bf7b,0xbec4bf6d,0xbec4bf6d,0x3f7b3e48,0x3f7b3e48,
  0x3ec43f6d,0x3ec43f6d,0xbe483f7b,0xbe483f7b,0xbf4e3f18,0x3f183f4e,0x3d493f80,0x3f80bd49,0x3f04bf5c,0xbf5cbf04,0xbf673edb,0x3edb3f67,
  0xbe163f7d,0x3f7d3e16,0xbf3ebf2c,0xbf2c3f3e,0xbe79bf78,0xbf783e79,0x3eacbf71,0xbf71beac,0x3f183f4e,0x3f4ebf18,0x3f80bd49,0xbd49bf80,
  0xbf5cbf04,0xbf043f5c,0x3edb3f67,0x3f67bedb,0x3f7d3e16,0x3e16bf7d,0xbf2c3f3e,0x3f3e3f2c,0xbf783e79,0x3e793f78,0xbf71beac,0xbeac3f71,
  0x3f22bf46,0xbf223f46,0xbe95bf75,0x3e953f75,0x3dc93f7f,0xbdc9bf7f,0x3ef1bf62,0xbef13f62,0xbf46bf22,0x3f463f22,0x3f75be95,0xbf753e95,
  0x3f7fbdc9,0xbf7f3dc9,0x3f623ef1,0xbf62bef1,0xbf46bf22,0x3f463f22,0xbf753e95,0x3f75be95,0x3f7fbdc9,0xbf7f3dc9,0xbf62bef1,0x3f623ef1,
  0xbf223f46,0x3f22bf46,0xbe95bf75,0x3e953f75,0xbdc9bf7f,0x3dc93f7f,0x3ef1bf62,0xbef13f62,0xbedb3f67,0xbf67bedb,0x3f043f5c,0xbf5c3f04,
  0xbf2cbf3e,0x3f3ebf2c,0x3e163f7d,0xbf7d3e16,0x3f71beac,0x3eac3f71,0xbe793f78,0xbf78be79,0xbd493f80,0xbf80bd49,0xbf183f4e,0xbf4ebf18,
  0x3f673edb,0xbedb3f67,0x3f5cbf04,0x3f043f5c,0xbf3e3f2c,0xbf2cbf3e,0x3f7dbe16,0x3e163f7d,0xbeacbf71,0x3f71beac,0x3f783e79,0xbe793f78,
  0x3f803d49,0xbd493f80,0x3f4e3f18,0xbf183f4e,0x3f80,0x3f80,0x3f6d3ec4,0x3f6d3ec4,0x3f80,0x3f80,0x3ec4bf6d,0x3ec4bf6d,
  0x3f80,0x3f80,0xbf6dbec4,0xbf6dbec4,0x3f80,0x3f80,0xbec43f6d,0xbec43f6d,0x3f808000,0x3f808000,0x3ec4bf6d,0x3ec4bf6d,
  0x3f808000,0x3f808000,0xbf6dbec4,0xbf6dbec4,0x3f808000,0x3f808000,0xbec43f6d,0xbec43f6d,0x3f808000,0x3f808000,0x3f6d3ec4,0x3f6d3ec4,
  0x3e953f75,0x3f75be95,0x3f7f3dc9,0x3dc9bf7f,0x3f223f46,0x3f46bf22,0xbe95bf75,0xbf753e95,0x3f623ef1,0x3ef1bf62,0xbf463f22,0x3f223f46,
  0x3f7f3dc9,0x3dc9bf7f,0x3f623ef1,0x3ef1bf62,0x3f75be95,0xbe95bf75,0x3dc9bf7f,0xbf7fbdc9,0x3f46bf22,0xbf22bf46,0xbf753e95,0x3e953f75,
  0x3ef1bf62,0xbf62bef1,0x3f223f46,0x3f46bf22,0x3dc9bf7f,0xbf7fbdc9,0x3ef1bf62,0xbf62bef1,0x3f0e3f55,0xbf0ebf55,0x3f7bbe48,0xbf7b3e48,
  0x3f7b3e48,0xbf7bbe48,0xbf55bf0e,0x3f553f0e,0x3f55bf0e,0xbf553f0e,0x3e483f7b,0xbe48bf7b,0x3e48bf7b,0xbe483f7b,0x3f0ebf55,0xbf0e3f55,
  0x3f55bf0e,0xbf553f0e,0xbe48bf7b,0x3e483f7b,0x3e48bf7b,0xbe483f7b,0xbf0e3f55,0x3f0ebf55,0xbf0ebf55,0x3f0e3f55,0x3f7bbe48,0xbf7b3e48,
  0xbf7bbe48,0x3f7b3e48,0xbf55bf0e,0x3f553f0e,0x3f463f22,0xbf223f46,0x3f62bef1,0x3ef13f62,0x3f62bef1,0x3ef13f62,0xbf7f3dc9,0xbdc9bf7f,
  0xbdc9bf7f,0x3f7fbdc9,0x3f753e95,0xbe953f75,0xbf75be95,0x3e95bf75,0xbf46bf22,0x3f22bf46,0x3f22bf46,0x3f463f22,0xbef1bf62,0x3f62bef1,
  0xbef1bf62,0x3f62bef1,0x3dc93f7f,0xbf7f3dc9,0xbf7f3dc9,0xbdc9bf7f,0x3e95bf75,0x3f753e95,0xbe953f75,0xbf75be95,0xbf223f46,0xbf46bf22,
  0x3f35bf35,0x3f35bf35,0xbec4bf6d,0xbec4bf6d,0xbf353f35,0xbf353f35,0x3f6dbec4,0x3f6dbec4,0x3f35bf35,0x3f35bf35,0x3ec43f6d,0x3ec43f6d,
  0xbf353f35,0xbf353f35,0xbf6d3ec4,0xbf6d3ec4,0xbf35bf35,0xbf35bf35,0xbf6d3ec4,0xbf6d3ec4,0x3f353f35,0x3f353f35,0xbec4bf6d,0xbec4bf6d,
  0xbf35bf35,0xbf35bf35,0x3f6dbec4,0x3f6dbec4,0x3f353f35,0x3f353f35,0x3ec43f6d,0x3ec43f6d,0x3ef1bf62,0xbf62bef1,0xbf22bf46,0xbf463f22,
  0xbdc93f7f,0x3f7f3dc9,0x3ef1bf62,0xbf62bef1,0xbe95bf75,0xbf753e95,0x3f7f3dc9,0x3dc9bf7f,0x3f223f46,0x3f46bf22,0x3e953f75,0x3f75be95,
  0xbf62bef1,0xbef13f62,0xbf463f22,0x3f223f46,0x3f7f3dc9,0x3dc9bf7f,0xbf62bef1,0xbef13f62,0xbf753e95,0x3e953f75,0x3dc9bf7f,0xbf7fbdc9,
  0x3f46bf22,0xbf22bf46,0x3f75be95,0xbe95bf75,0x3e48bf7b,0xbe483f7b,0xbf55bf0e,0x3f553f0e,0x3f0e3f55,0xbf0ebf55,0xbe48bf7b,0x3e483f7b,
  0xbf7bbe48,0x3f7b3e48,0x3f0ebf55,0xbf0e3f55,0x3f55bf0e,0xbf553f0e,0x3f7bbe48,0xbf7b3e48,0xbf7bbe48,0x3f7b3e48,0xbf0e3f55,0x3f0ebf55,
  0x3f55bf0e,0xbf553f0e,0xbf7b3e48,0x3f7bbe48,0xbe483f7b,0x3e48bf7b,0xbf55bf0e,0x3f553f0e,0xbf0ebf55,0x3f0e3f55,0xbe48bf7b,0x3e483f7b,
  0xbdc9bf7f,0x3f7fbdc9,0xbf75be95,0x3e95bf75,0x3f753e95,0xbe953f75,0xbf46bf22,0x3f22bf46,0xbf223f46,0xbf46bf22,0xbef1bf62,0x3f62bef1,
  0xbef1bf62,0x3f62bef1,0xbdc9bf7f,0x3f7fbdc9,0xbf7f3dc9,0xbdc9bf7f,0xbe953f75,0xbf75be95,0x3e95bf75,0x3f753e95,0xbf223f46,0xbf46bf22,
  0x3f463f22,0xbf223f46,0xbf623ef1,0xbef1bf62,0xbf623ef1,0xbef1bf62,0xbf7f3dc9,0xbdc9bf7f,0x3f80,0x3f80,0x3f6d3ec4,0x3f6d3ec4,
  0x3f80,0x3f80,0x3ec4bf6d,0x3ec4bf6d,0x3f80,0x3f80,0xbf6dbec4,0xbf6dbec4,0x3f80,0x3f80,0xbec43f6d,0xbec43f6d,
  0x3f808000,0x3f808000,0x3ec4bf6d,0x3ec4bf6d,0x3f808000,0x3f808000,0xbf6dbec4,0xbf6dbec4,0x3f808000,0x3f808000,0xbec43f6d,0xbec43f6d,
  0x3f808000,0x3f808000,0x3f6d3ec4,0x3f6d3ec4,0xbe95bf75,0xbf753e95,0xbf7fbdc9,0xbdc93f7f,0xbf22bf46,0xbf463f22,0x3e953f75,0x3f75be95,
  0xbf62bef1,0xbef13f62,0x3f46bf22,0xbf22bf46,0xbf7fbdc9,0xbdc93f7f,0xbf62bef1,0xbef13f62,0xbf753e95,0x3e953f75,0xbdc93f7f,0x3f7f3dc9,
  0xbf463f22,0x3f223f46,0x3f75be95,0xbe95bf75,0xbef13f62,0x3f623ef1,0xbf22bf46,0xbf463f22,0xbdc93f7f,0x3f7f3dc9,0xbef13f62,0x3f623ef1,
  0x3f0e3f55,0xbf0ebf55,0x3f7bbe48,0xbf7b3e48,0x3f7b3e48,0xbf7bbe48,0xbf55bf0e,0x3f553f0e,0x3f55bf0e,0xbf553f0e,0x3e483f7b,0xbe48bf7b,
  0x3e48bf7b,0xbe483f7b,0x3f0ebf55,0xbf0e3f55,0x3f55bf0e,0xbf553f0e,0xbe48bf7b,0x3e483f7b,0x3e48bf7b,0xbe483f7b,0xbf0e3f55,0x3f0ebf55,
  0xbf0ebf55,0x3f0e3f55,0x3f7bbe48,0xbf7b3e48,0xbf7bbe48,0x3f7b3e48,0xbf55bf0e,0x3f553f0e,0xbf46bf22,0x3f22bf46,0xbf623ef1,0xbef1bf62,
  0xbf623ef1,0xbef1bf62,0x3f7fbdc9,0x3dc93f7f,0x3dc93f7f,0xbf7f3dc9,0xbf75be95,0x3e95bf75,0x3f753e95,0xbe953f75,0x3f463f22,0xbf223f46,
  0xbf223f46,0xbf46bf22,0x3ef13f62,0xbf623ef1,0x3ef13f62,0xbf623ef1,0xbdc9bf7f,0x3f7fbdc9,0x3f7fbdc9,0x3dc93f7f,0xbe953f75,0xbf75be95,
  0x3e95bf75,0x3f753e95,0x3f22bf46,0x3f463f22,0x3f35bf35,0x3f35bf35,0xbec4bf6d,0xbec4bf6d,0xbf353f35,0xbf353f35,0x3f6dbec4,0x3f6dbec4,
  0x3f35bf35,0x3f35bf35,0x3ec43f6d,0x3ec43f6d,0xbf353f35,0xbf353f35,0xbf6d3ec4,0xbf6d3ec4,0xbf35bf35,0xbf35bf35,0xbf6d3ec4,0xbf6d3ec4,
  0x3f353f35,0x3f353f35,0xbec4bf6d,0xbec4bf6d,0xbf35bf35,0xbf35bf35,0x3f6dbec4,0x3f6dbec4,0x3f353f35,0x3f353f35,0x3ec43f6d,0x3ec43f6d,
  0xbef13f62,0x3f623ef1,0x3f223f46,0x3f46bf22,0x3dc9bf7f,0xbf7fbdc9,0xbef13f62,0x3f623ef1,0x3e953f75,0x3f75be95,0xbf7fbdc9,0xbdc93f7f,
  0xbf22bf46,0xbf463f22,0xbe95bf75,0xbf753e95,0x3f623ef1,0x3ef1bf62,0x3f46bf22,0xbf22bf46,0xbf7fbdc9,0xbdc93f7f,0x3f623ef1,0x3ef1bf62,
  0x3f75be95,0xbe95bf75,0xbdc93f7f,0x3f7f3dc9,0xbf463f22,0x3f223f46,0xbf753e95,0x3e953f75,0x3e48bf7b,0xbe483f7b,0xbf55bf0e,0x3f553f0e,
  0x3f0e3f55,0xbf0ebf55,0xbe48bf7b,0x3e483f7b,0xbf7bbe48,0x3f7b3e48,0x3f0ebf55,0xbf0e3f55,0x3f55bf0e,0xbf553f0e,0x3f7bbe48,0xbf7b3e48,
  0xbf7bbe48,0x3f7b3e48,0xbf0e3f55,0x3f0ebf55,0x3f55bf0e,0xbf553f0e,0xbf7b3e48,0x3f7bbe48,0xbe483f7b,0x3e48bf7b,0xbf55bf0e,0x3f553f0e,
  0xbf0ebf55,0x3f0e3f55,0xbe48bf7b,0x3e483f7b,0x3dc93f7f,0xbf7f3dc9,0x3f753e95,0xbe953f75,0xbf75be95,0x3e95bf75,0x3f463f22,0xbf223f46,
  0x3f22bf46,0x3f463f22,0x3ef13f62,0xbf623ef1,0x3ef13f62,0xbf623ef1,0x3dc93f7f,0xbf7f3dc9,0x3f7fbdc9,0x3dc93f7f,0x3e95bf75,0x3f753e95,
  0xbe953f75,0xbf75be95,0x3f22bf46,0x3f463f22,0xbf46bf22,0x3f22bf46,0x3f62bef1,0x3ef13f62,0x3f62bef1,0x3ef13f62,0x3f7fbdc9,0x3dc93f7f,
  0x3f80,0x3f80,0x3f7b3e48,0x3f7b3e48,0x3f80,0x3f80,0x3e48bf7b,0x3e48bf7b,0x3f80,0x3f80,0xbf7bbe48,0xbf7bbe48,
  0x3f80,0x3f80,0xbe483f7b,0xbe483f7b,0x3f808000,0x3f808000,0x3e48bf7b,0x3e48bf7b,0x3f808000,0x3f808000,0xbf7bbe48,0xbf7bbe48,
  0x3f808000,0x3f808000,0xbe483f7b,0xbe483f7b,0x3f808000,0x3f808000,0x3f7b3e48,0x3f7b3e48,0x3eac3f71,0x3f71beac,0x3f7dbe16,0xbe16bf7d,
  0x3f2c3f3e,0x3f3ebf2c,0xbf04bf5c,0xbf5c3f04,0x3f673edb,0x3edbbf67,0xbf183f4e,0x3f4e3f18,0x3f803d49,0x3d49bf80,0x3f783e79,0x3e79bf78,
  0x3f71beac,0xbeacbf71,0xbe16bf7d,0xbf7d3e16,0x3f3ebf2c,0xbf2cbf3e,0xbf5c3f04,0x3f043f5c,0x3edbbf67,0xbf67bedb,0x3f4e3f18,0x3f18bf4e,
  0x3d49bf80,0xbf80bd49,0x3e79bf78,0xbf78be79,0x3f223f46,0xbf22bf46,0x3f62bef1,0xbf623ef1,0x3f7f3dc9,0xbf7fbdc9,0xbf75be95,0x3f753e95,
  0x3f46bf22,0xbf463f22,0x3ef13f62,0xbef1bf62,0x3dc9bf7f,0xbdc93f7f,0x3e95bf75,0xbe953f75,0x3f46bf22,0xbf463f22,0xbef1bf62,0x3ef13f62,
  0x3dc9bf7f,0xbdc93f7f,0xbe953f75,0x3e95bf75,0xbf22bf46,0x3f223f46,0x3f62bef1,0xbf623ef1,0xbf7fbdc9,0x3f7f3dc9,0xbf75be95,0x3f753e95,
  0x3f5c3f04,0xbf043f5c,0x3f2cbf3e,0x3f3e3f2c,0x3f4ebf18,0x3f183f4e,0xbf673edb,0xbedbbf67,0xbe79bf78,0x3f78be79,0x3f80bd49,0x3d493f80,
  0xbf7dbe16,0x3e16bf7d,0xbf71beac,0x3eacbf71,0x3f04bf5c,0x3f5c3f04,0xbf3ebf2c,0x3f2cbf3e,0xbf18bf4e,0x3f4ebf18,0x3edb3f67,0xbf673edb,
  0xbf783e79,0xbe79bf78,0xbd49bf80,0x3f80bd49,0xbe163f7d,0xbf7dbe16,0xbeac3f71,0xbf71beac,0x3ec4bf6d,0x3ec4bf6d,0xbf55bf0e,0xbf55bf0e,
  0xbec43f6d,0xbec43f6d,0x3f0ebf55,0x3f0ebf55,0x3ec4bf6d,0x3ec4bf6d,0x3f553f0e,0x3f553f0e,0xbec43f6d,0xbec43f6d,0xbf0e3f55,0xbf0e3f55,
  0xbf6dbec4,0xbf6dbec4,0xbf0e3f55,0xbf0e3f55,0x3f6d3ec4,0x3f6d3ec4,0xbf55bf0e,0xbf55bf0e,0xbf6dbec4,0xbf6dbec4,0x3f0ebf55,0x3f0ebf55,
  0x3f6d3ec4,0x3f6d3ec4,0x3f553f0e,0x3f553f0e,0x3d49bf80,0xbf80bd49,0xbf78be79,0xbe793f78,0x3eac3f71,0x3f71beac,0xbe16bf7d,0xbf7d3e16,
  0xbf2cbf3e,0xbf3e3f2c,0x3f5cbf04,0xbf04bf5c,0x3f673edb,0x3edbbf67,0x3f4e3f18,0x3f18bf4e,0xbf80bd49,0xbd493f80,0xbe793f78,0x3f783e79,
  0x3f71beac,0xbeacbf71,0xbf7d3e16,0x3e163f7d,0xbf3e3f2c,0x3f2c3f3e,0xbf04bf5c,0xbf5c3f04,0x3edbbf67,0xbf67bedb,0x3f18bf4e,0xbf4ebf18,
  0xbe95bf75,0x3e953f75,0xbf7f3dc9,0x3f7fbdc9,0x3f623ef1,0xbf62bef1,0xbf46bf22,0x3f463f22,0xbf753e95,0x3f75be95,0xbdc9bf7f,0x3dc93f7f,
  0x3ef1bf62,0xbef13f62,0x3f22bf46,0xbf223f46,0xbf753e95,0x3f75be95,0x3dc93f7f,0xbdc9bf7f,0x3ef1bf62,0xbef13f62,0xbf223f46,0x3f22bf46,
  0x3e953f75,0xbe95bf75,0xbf7f3dc9,0x3f7fbdc9,0xbf62bef1,0x3f623ef1,0xbf46bf22,0x3f463f22,0xbf18bf4e,0x3f4ebf18,0xbf673edb,0xbedbbf67,
  0x3f78be79,0x3e793f78,0xbf803d49,0xbd49bf80,0xbe163f7d,0xbf7dbe16,0xbf71beac,0x3eacbf71,0xbf5cbf04,0x3f04bf5c,0xbf3ebf2c,0x3f2cbf3e,
  0xbf4e3f18,0xbf18bf4e,0x3edb3f67,0xbf673edb,0xbe79bf78,0x3f78be79,0x3d493f80,0xbf803d49,0x3f7d3e16,0xbe163f7d,0xbeac3f71,0xbf71beac,
  0xbf043f5c,0xbf5cbf04,0xbf2c3f3e,0xbf3ebf2c,0x3f80,0x3f80,0x3f7b3e48,0x3f7b3e48,0x3f80,0x3f80,0x3e48bf7b,0x3e48bf7b,
  0x3f80,0x3f80,0xbf7bbe48,0xbf7bbe48,0x3f80,0x3f80,0xbe483f7b,0xbe483f7b,0x3f808000,0x3f808000,0x3e48bf7b,0x3e48bf7b,
  0x3f808000,0x3f808000,0xbf7bbe48,0xbf7bbe48,0x3f808000,0x3f808000,0xbe483f7b,0xbe483f7b,0x3f808000,0x3f808000,0x3f7b3e48,0x3f7b3e48,
  0xbeacbf71,0xbf713eac,0xbf7d3e16,0x3e163f7d,0xbf2cbf3e,0xbf3e3f2c,0x3f043f5c,0x3f5cbf04,0xbf67bedb,0xbedb3f67,0x3f18bf4e,0xbf4ebf18,
  0xbf80bd49,0xbd493f80,0xbf78be79,0xbe793f78,0xbf713eac,0x3eac3f71,0x3e163f7d,0x3f7dbe16,0xbf3e3f2c,0x3f2c3f3e,0x3f5cbf04,0xbf04bf5c,
  0xbedb3f67,0x3f673edb,0xbf4ebf18,0xbf183f4e,0xbd493f80,0x3f803d49,0xbe793f78,0x3f783e79,0x3f223f46,0xbf22bf46,0x3f62bef1,0xbf623ef1,
  0x3f7f3dc9,0xbf7fbdc9,0xbf75be95,0x3f753e95,0x3f46bf22,0xbf463f22,0x3ef13f62,0xbef1bf62,0x3dc9bf7f,0xbdc93f7f,0x3e95bf75,0xbe953f75,
  0x3f46bf22,0xbf463f22,0xbef1bf62,0x3ef13f62,0x3dc9bf7f,0xbdc93f7f,0xbe953f75,0x3e95bf75,0xbf22bf46,0x3f223f46,0x3f62bef1,0xbf623ef1,
  0xbf7fbdc9,0x3f7f3dc9,0xbf75be95,0x3f753e95,0xbf5cbf04,0x3f04bf5c,0xbf2c3f3e,0xbf3ebf2c,0xbf4e3f18,0xbf18bf4e,0x3f67bedb,0x3edb3f67,
  0x3e793f78,0xbf783e79,0xbf803d49,0xbd49bf80,0x3f7d3e16,0xbe163f7d,0x3f713eac,0xbeac3f71,0xbf043f5c,0xbf5cbf04,0x3f3e3f2c,0xbf2c3f3e,
  0x3f183f4e,0xbf4e3f18,0xbedbbf67,0x3f67bedb,0x3f78be79,0x3e793f78,0x3d493f80,0xbf803d49,0x3e16bf7d,0x3f7d3e16,0x3eacbf71,0x3f713eac,
  0x3ec4bf6d,0x3ec4bf6d,0xbf55bf0e,0xbf55bf0e,0xbec43f6d,0xbec43f6d,0x3f0ebf55,0x3f0ebf55,0x3ec4bf6d,0x3ec4bf6d,0x3f553f0e,0x3f553f0e,
  0xbec43f6d,0xbec43f6d,0xbf0e3f55,0xbf0e3f55,0xbf6dbec4,0xbf6dbec4,0xbf0e3f55,0xbf0e3f55,0x3f6d3ec4,0x3f6d3ec4,0xbf55bf0e,0xbf55bf0e,
  0xbf6dbec4,0xbf6dbec4,0x3f0ebf55,0x3f0ebf55,0x3f6d3ec4,0x3f6d3ec4,0x3f553f0e,0x3f553f0e,0xbd493f80,0x3f803d49,0x3f783e79,0x3e79bf78,
  0xbeacbf71,0xbf713eac,0x3e163f7d,0x3f7dbe16,0x3f2c3f3e,0x3f3ebf2c,0xbf5c3f04,0x3f043f5c,0xbf67bedb,0xbedb3f67,0xbf4ebf18,0xbf183f4e,
  0x3f803d49,0x3d49bf80,0x3e79bf78,0xbf78be79,0xbf713eac,0x3eac3f71,0x3f7dbe16,0xbe16bf7d,0x3f3ebf2c,0xbf2cbf3e,0x3f043f5c,0x3f5cbf04,
  0xbedb3f67,0x3f673edb,0xbf183f4e,0x3f4e3f18,0xbe95bf75,0x3e953f75,0xbf7f3dc9,0x3f7fbdc9,0x3f623ef1,0xbf62bef1,0xbf46bf22,0x3f463f22,
  0xbf753e95,0x3f75be95,0xbdc9bf7f,0x3dc93f7f,0x3ef1bf62,0xbef13f62,0x3f22bf46,0xbf223f46,0xbf753e95,0x3f75be95,0x3dc93f7f,0xbdc9bf7f,
  0x3ef1bf62,0xbef13f62,0xbf223f46,0x3f22bf46,0x3e953f75,0xbe95bf75,0xbf7f3dc9,0x3f7fbdc9,0xbf62bef1,0x3f623ef1,0xbf46bf22,0x3f463f22,
  0x3f183f4e,0xbf4e3f18,0x3f67bedb,0x3edb3f67,0xbf783e79,0xbe79bf78,0x3f80bd49,0x3d493f80,0x3e16bf7d,0x3f7d3e16,0x3f713eac,0xbeac3f71,
  0x3f5c3f04,0xbf043f5c,0x3f3e3f2c,0xbf2c3f3e,0x3f4ebf18,0x3f183f4e,0xbedbbf67,0x3f67bedb,0x3e793f78,0xbf783e79,0xbd49bf80,0x3f80bd49,
  0xbf7dbe16,0x3e16bf7d,0x3eacbf71,0x3f713eac,0x3f04bf5c,0x3f5c3f04,0x3f2cbf3e,0x3f3e3f2c,0x3f80,0x3f80,0x3f80,0x3f80,
  0x3f80,0x3f80,0x3f800000,0x3f800000,0x3f80,0x3f80,0xbf80,0xbf80,0x3f80,0x3f80,0xbf800000,0xbf800000,
  0x3f808000,0x3f808000,0x3f808000,0x3f808000,0x3f808000,0x3f808000,0xbf80,0xbf80,0x3f808000,0x3f808000,0xbf808000,0xbf808000,
  0x3f808000,0x3f808000,0x3f80,0x3f80,0x3f80,0x3f800000,0x3f80,0x3f800000,0x3ec43f6d,0x3f6dbec4,0x3f6dbec4,0xbec4bf6d,
  0x3f353f35,0x3f35bf35,0xbf35bf35,0xbf353f35,0x3f6d3ec4,0x3ec4bf6d,0xbec43f6d,0x3f6d3ec4,0x3f808000,0xbf80,0x3f808000,0xbf80,
  0x3f6dbec4,0xbec4bf6d,0xbec4bf6d,0xbf6d3ec4,0x3f35bf35,0xbf35bf35,0xbf353f35,0x3f353f35,0x3ec4bf6d,0xbf6dbec4,0x3f6d3ec4,0x3ec4bf6d,
  0x3f80,0xbf80,0x3f80,0xbf80,0x3f353f35,0xbf35bf35,0x3f35bf35,0xbf353f35,0x3f800000,0xbf800000,0xbf800000,0x3f800000,
  0x3f35bf35,0xbf353f35,0x3f353f35,0xbf35bf35,0x3f808000,0xbf808000,0x3f808000,0xbf808000,0x3f35bf35,0xbf353f35,0xbf35bf35,0x3f353f35,
  0xbf80,0x3f80,0x3f80,0xbf80,0xbf35bf35,0x3f353f35,0x3f35bf35,0xbf353f35,0x3f80,0xbf800000,0x3f80,0xbf800000,
  0x3f6d3ec4,0xbec43f6d,0x3ec4bf6d,0x3f6d3ec4,0x3f35bf35,0x3f353f35,0xbf353f35,0xbf35bf35,0xbec4bf6d,0x3f6dbec4,0x3f6dbec4,0x3ec43f6d,
  0x3f808000,0x3f80,0x3f808000,0x3f80,0x3ec4bf6d,0x3f6d3ec4,0xbf6dbec4,0x3ec4bf6d,0xbf35bf35,0x3f35bf35,0x3f353f35,0xbf353f35,
  0xbf6d3ec4,0xbec4bf6d,0xbec4bf6d,0x3f6dbec4,0x3f80,0x3f80,0x3f80,0x3f80,0xbf80,0xbf80,0xbf800000,0xbf800000,
  0x3f80,0x3f80,0xbf80,0xbf80,0xbf80,0xbf80,0x3f800000,0x3f800000,0x3f808000,0x3f808000,0x3f808000,0x3f808000,
  0xbf808000,0xbf808000,0x3f80,0x3f80,0x3f808000,0x3f808000,0xbf808000,0xbf808000,0xbf808000,0xbf808000,0xbf80,0xbf80,
  0x3f80,0x3f800000,0x3f80,0x3f800000,0xbec4bf6d,0xbf6d3ec4,0xbf6d3ec4,0x3ec43f6d,0x3f353f35,0x3f35bf35,0xbf35bf35,0xbf353f35,
  0xbf6dbec4,0xbec43f6d,0x3ec4bf6d,0xbf6dbec4,0x3f808000,0xbf80,0x3f808000,0xbf80,0xbf6d3ec4,0x3ec43f6d,0x3ec43f6d,0x3f6dbec4,
  0x3f35bf35,0xbf35bf35,0xbf353f35,0x3f353f35,0xbec43f6d,0x3f6d3ec4,0xbf6dbec4,0xbec43f6d,0x3f80,0xbf80,0x3f80,0xbf80,
  0xbf35bf35,0x3f353f35,0xbf353f35,0x3f35bf35,0x3f800000,0xbf800000,0xbf800000,0x3f800000,0xbf353f35,0x3f35bf35,0xbf35bf35,0x3f353f35,
  0x3f808000,0xbf808000,0x3f808000,0xbf808000,0xbf353f35,0x3f35bf35,0x3f353f35,0xbf35bf35,0xbf80,0x3f80,0x3f80,0xbf80,
  0x3f353f35,0xbf35bf35,0xbf353f35,0x3f35bf35,0x3f80,0xbf800000,0x3f80,0xbf800000,0xbf6dbec4,0x3ec4bf6d,0xbec43f6d,0xbf6dbec4,
  0x3f35bf35,0x3f353f35,0xbf353f35,0xbf35bf35,0x3ec43f6d,0xbf6d3ec4,0xbf6d3ec4,0xbec4bf6d,0x3f808000,0x3f80,0x3f808000,0x3f80,
  0xbec43f6d,0xbf6dbec4,0x3f6d3ec4,0xbec43f6d,0xbf35bf35,0x3f35bf35,0x3f353f35,0xbf353f35,0x3f6dbec4,0x3ec43f6d,0x3ec43f6d,0xbf6d3ec4,
  0x3f80,0x3f80,0x3f80,0x3f80,0x3f80,0x3f80,0x3f800000,0x3f800000,0x3f80,0x3f80,0xbf80,0xbf80,
  0x3f80,0x3f80,0xbf800000,0xbf800000,0x3f808000,0x3f808000,0x3f808000,0x3f808000,0x3f808000,0x3f808000,0xbf80,0xbf80,
  0x3f808000,0x3f808000,0xbf808000,0xbf808000,0x3f808000,0x3f808000,0x3f80,0x3f80,0xbf80,0xbf800000,0xbf80,0xbf800000,
  0xbec4bf6d,0xbf6d3ec4,0xbf6d3ec4,0x3ec43f6d,0xbf35bf35,0xbf353f35,0x3f353f35,0x3f35bf35,0xbf6dbec4,0xbec43f6d,0x3ec4bf6d,0xbf6dbec4,
  0xbf808000,0x3f80,0xbf808000,0x3f80,0xbf6d3ec4,0x3ec43f6d,0x3ec43f6d,0x3f6dbec4,0xbf353f35,0x3f353f35,0x3f35bf35,0xbf35bf35,
  0xbec43f6d,0x3f6d3ec4,0xbf6dbec4,0xbec43f6d,0x3f80,0xbf80,0x3f80,0xbf80,0x3f353f35,0xbf35bf35,0x3f35bf35,0xbf353f35,
  0x3f800000,0xbf800000,0xbf800000,0x3f800000,0x3f35bf35,0xbf353f35,0x3f353f35,0xbf35bf35,0x3f808000,0xbf808000,0x3f808000,0xbf808000,
  0x3f35bf35,0xbf353f35,0xbf35bf35,0x3f353f35,0xbf80,0x3f80,0x3f80,0xbf80,0xbf35bf35,0x3f353f35,0x3f35bf35,0xbf353f35,
  0xbf80,0x3f800000,0xbf80,0x3f800000,0xbf6dbec4,0x3ec4bf6d,0xbec43f6d,0xbf6dbec4,0xbf353f35,0xbf35bf35,0x3f35bf35,0x3f353f35,
  0x3ec43f6d,0xbf6d3ec4,0xbf6d3ec4,0xbec4bf6d,0xbf808000,0xbf80,0xbf808000,0xbf80,0xbec43f6d,0xbf6dbec4,0x3f6d3ec4,0xbec43f6d,
  0x3f353f35,0xbf353f35,0xbf35bf35,0x3f35bf35,0x3f6dbec4,0x3ec43f6d,0x3ec43f6d,0xbf6d3ec4,0x3f80,0x3f80,0x3f80,0x3f80,
  0xbf80,0xbf80,0xbf800000,0xbf800000,0x3f80,0x3f80,0xbf80,0xbf80,0xbf80,0xbf80,0x3f800000,0x3f800000,
  0x3f808000,0x3f808000,0x3f808000,0x3f808000,0xbf808000,0xbf808000,0x3f80,0x3f80,0x3f808000,0x3f808000,0xbf808000,0xbf808000,
  0xbf808000,0xbf808000,0xbf80,0xbf80,0xbf80,0xbf800000,0xbf80,0xbf800000,0x3ec43f6d,0x3f6dbec4,0x3f6dbec4,0xbec4bf6d,
  0xbf35bf35,0xbf353f35,0x3f353f35,0x3f35bf35,0x3f6d3ec4,0x3ec4bf6d,0xbec43f6d,0x3f6d3ec4,0xbf808000,0x3f80,0xbf808000,0x3f80,
  0x3f6dbec4,0xbec4bf6d,0xbec4bf6d,0xbf6d3ec4,0xbf353f35,0x3f353f35,0x3f35bf35,0xbf35bf35,0x3ec4bf6d,0xbf6dbec4,0x3f6d3ec4,0x3ec4bf6d,
  0x3f80,0xbf80,0x3f80,0xbf80,0xbf35bf35,0x3f353f35,0xbf353f35,0x3f35bf35,0x3f800000,0xbf800000,0xbf800000,0x3f800000,
  0xbf353f35,0x3f35bf35,0xbf35bf35,0x3f353f35,0x3f808000,0xbf808000,0x3f808000,0xbf808000,0xbf353f35,0x3f35bf35,0x3f353f35,0xbf35bf35,
  0xbf80,0x3f80,0x3f80,0xbf80,0x3f353f35,0xbf35bf35,0xbf353f35,0x3f35bf35,0xbf80,0x3f800000,0xbf80,0x3f800000,
  0x3f6d3ec4,0xbec43f6d,0x3ec4bf6d,0x3f6d3ec4,0xbf353f35,0xbf35bf35,0x3f35bf35,0x3f353f35,0xbec4bf6d,0x3f6dbec4,0x3f6dbec4,0x3ec43f6d,
  0xbf808000,0xbf80,0xbf808000,0xbf80,0x3ec4bf6d,0x3f6d3ec4,0xbf6dbec4,0x3ec4bf6d,0x3f353f35,0xbf353f35,0xbf35bf35,0x3f35bf35,
  0xbf6d3ec4,0xbec4bf6d,0xbec4bf6d,0x3f6dbec4,0x3f80,0x3e483f7b,0x3f80,0x3e483f7b,0x3d493f80,0x3e793f78,0x3f80bd49,0x3f78be79,
  0x3dc93f7f,0x3e953f75,0xbdc9bf7f,0xbe95bf75,0x3e163f7d,0x3eac3f71,0xbf7d3e16,0xbf713eac,0x3f808000,0x3f7bbe48,0x3f808000,0x3f7bbe48,
  0x3f80bd49,0x3f78be79,0xbd49bf80,0xbe79bf78,0x3f7fbdc9,0x3f75be95,0xbf7f3dc9,0xbf753e95,0x3f7dbe16,0x3f71beac,0x3e163f7d,0x3eac3f71,
  0x3f80,0x3f7bbe48,0x3f80,0x3f7bbe48,0x3edb3f67,0x3f4ebf18,0x3f67bedb,0xbf18bf4e,0x3f463f22,0x3ef1bf62,0xbf46bf22,0xbef13f62,
  0x3f783e79,0x3d49bf80,0xbe793f78,0x3f803d49,0x3f808000,0xbe48bf7b,0x3f808000,0xbe48bf7b,0x3f67bedb,0xbf18bf4e,0xbedbbf67,0xbf4e3f18,
  0x3f22bf46,0xbf62bef1,0xbf223f46,0x3f623ef1,0x3e79bf78,0xbf80bd49,0x3f783e79,0x3d49bf80,0x3f80,0xbe48bf7b,0x3f80,0xbe48bf7b,
  0x3f3e3f2c,0xbf5cbf04,0x3f2cbf3e,0xbf043f5c,0x3f7fbdc9,0xbf753e95,0xbf7f3dc9,0x3f75be95,0x3f18bf4e,0xbedb3f67,0x3f4e3f18,0xbf67bedb,
  0x3f808000,0xbf7b3e48,0x3f808000,0xbf7b3e48,0x3f2cbf3e,0xbf043f5c,0xbf3ebf2c,0x3f5c3f04,0xbdc9bf7f,0x3e953f75,0x3dc93f7f,0xbe95bf75,
  0xbf4ebf18,0x3f673edb,0x3f18bf4e,0xbedb3f67,0x3f80,0xbf7b3e48,0x3f80,0xbf7b3e48,0x3f713eac,0xbe163f7d,0x3eacbf71,0x3f7d3e16,
  0x3f22bf46,0x3f623ef1,0xbf223f46,0xbf62bef1,0xbf04bf5c,0x3f3ebf2c,0x3f5cbf04,0x3f2c3f3e,0x3f808000,0x3e483f7b,0x3f808000,0x3e483f7b,
  0x3eacbf71,0x3f7d3e16,0xbf71beac,0x3e16bf7d,0xbf46bf22,0x3ef1bf62,0x3f463f22,0xbef13f62,0xbf5c3f04,0xbf2cbf3e,0xbf04bf5c,0x3f3ebf2c,
  0x3f80,0x3e483f7b,0x3f80,0x3e483f7b,0xbd49bf80,0xbe79bf78,0xbf803d49,0xbf783e79,0x3dc93f7f,0x3e953f75,0xbdc9bf7f,0xbe95bf75,
  0xbe16bf7d,0xbeacbf71,0x3f7dbe16,0x3f71beac,0x3f808000,0x3f7bbe48,0x3f808000,0x3f7bbe48,0xbf803d49,0xbf783e79,0x3d493f80,0x3e793f78,
  0x3f7fbdc9,0x3f75be95,0xbf7f3dc9,0xbf753e95,0xbf7d3e16,0xbf713eac,0xbe16bf7d,0xbeacbf71,0x3f80,0x3f7bbe48,0x3f80,0x3f7bbe48,
  0xbedbbf67,0xbf4e3f18,0xbf673edb,0x3f183f4e,0x3f463f22,0x3ef1bf62,0xbf46bf22,0xbef13f62,0xbf78be79,0xbd493f80,0x3e79bf78,0xbf80bd49,
  0x3f808000,0xbe48bf7b,0x3f808000,0xbe48bf7b,0xbf673edb,0x3f183f4e,0x3edb3f67,0x3f4ebf18,0x3f22bf46,0xbf62bef1,0xbf223f46,0x3f623ef1,
  0xbe793f78,0x3f803d49,0xbf78be79,0xbd493f80,0x3f80,0xbe48bf7b,0x3f80,0xbe48bf7b,0xbf3ebf2c,0x3f5c3f04,0xbf2c3f3e,0x3f04bf5c,
  0x3f7fbdc9,0xbf753e95,0xbf7f3dc9,0x3f75be95,0xbf183f4e,0x3edbbf67,0xbf4ebf18,0x3f673edb,0x3f808000,0xbf7b3e48,0x3f808000,0xbf7b3e48,
  0xbf2c3f3e,0x3f04bf5c,0x3f3e3f2c,0xbf5cbf04,0xbdc9bf7f,0x3e953f75,0x3dc93f7f,0xbe95bf75,0x3f4e3f18,0xbf67bedb,0xbf183f4e,0x3edbbf67,
  0x3f80,0xbf7b3e48,0x3f80,0xbf7b3e48,0xbf71beac,0x3e16bf7d,0xbeac3f71,0xbf7dbe16,0x3f22bf46,0x3f623ef1,0xbf223f46,0xbf62bef1,
  0x3f043f5c,0xbf3e3f2c,0xbf5c3f04,0xbf2cbf3e,0x3f808000,0x3e483f7b,0x3f808000,0x3e483f7b,0xbeac3f71,0xbf7dbe16,0x3f713eac,0xbe163f7d,
  0xbf46bf22,0x3ef1bf62,0x3f463f22,0xbef13f62,0x3f5cbf04,0x3f2c3f3e,0x3f043f5c,0xbf3e3f2c,0x3ec43f6d,0x3f0e3f55,0x3ec43f6d,0x3f0e3f55,
  0x3edb3f67,0x3f183f4e,0x3f67bedb,0x3f4ebf18,0x3ef13f62,0x3f223f46,0xbef1bf62,0xbf22bf46,0x3f043f5c,0x3f2c3f3e,0xbf5c3f04,0xbf3e3f2c,
  0x3f6dbec4,0x3f55bf0e,0x3f6dbec4,0x3f55bf0e,0x3f67bedb,0x3f4ebf18,0xbedbbf67,0xbf18bf4e,0x3f62bef1,0x3f46bf22,0xbf623ef1,0xbf463f22,
  0x3f5cbf04,0x3f3ebf2c,0x3f043f5c,0x3f2c3f3e,0xbec4bf6d,0xbf553f0e,0xbec4bf6d,0xbf553f0e,0xbf3ebf2c,0xbf043f5c,0xbf2c3f3e,0x3f5c3f04,
  0xbf75be95,0xbdc93f7f,0x3f753e95,0x3dc9bf7f,0xbf7d3e16,0x3eac3f71,0xbe16bf7d,0xbf713eac,0xbf6d3ec4,0x3f0e3f55,0xbf6d3ec4,0x3f0e3f55,
  0xbf2c3f3e,0x3f5c3f04,0x3f3e3f2c,0x3f04bf5c,0xbe953f75,0x3f7f3dc9,0x3e95bf75,0xbf7fbdc9,0x3e163f7d,0x3f71beac,0xbf7d3e16,0x3eac3f71,
  0x3ec43f6d,0xbf0ebf55,0x3ec43f6d,0xbf0ebf55,0x3f713eac,0xbf7dbe16,0x3eacbf71,0xbe163f7d,0x3f62bef1,0xbf463f22,0xbf623ef1,0x3f46bf22,
  0x3e79bf78,0xbd493f80,0x3f783e79,0xbf80bd49,0x3f6dbec4,0xbf553f0e,0x3f6dbec4,0xbf553f0e,0x3eacbf71,0xbe163f7d,0xbf71beac,0x3f7d3e16,
  0xbef1bf62,0x3f223f46,0x3ef13f62,0xbf22bf46,0xbf78be79,0x3f803d49,0x3e79bf78,0xbd493f80,0xbec4bf6d,0x3f55bf0e,0xbec4bf6d,0x3f55bf0e,
  0xbf803d49,0xbe79bf78,0x3d493f80,0xbf783e79,0xbe953f75,0xbf7fbdc9,0x3e95bf75,0x3f7f3dc9,0x3f4e3f18,0xbedb3f67,0xbf183f4e,0xbf67bedb,
  0xbf6d3ec4,0xbf0ebf55,0xbf6d3ec4,0xbf0ebf55,0x3d493f80,0xbf783e79,0x3f80bd49,0x3e793f78,0x3f753e95,0xbdc93f7f,0xbf75be95,0x3dc9bf7f,
  0x3f18bf4e,0x3f673edb,0x3f4e3f18,0xbedb3f67,0x3ec43f6d,0x3f0e3f55,0x3ec43f6d,0x3f0e3f55,0xbedbbf67,0xbf18bf4e,0xbf673edb,0xbf4e3f18,
  0x3ef13f62,0x3f223f46,0xbef1bf62,0xbf22bf46,0xbf04bf5c,0xbf2cbf3e,0x3f5cbf04,0x3f3ebf2c,0x3f6dbec4,0x3f55bf0e,0x3f6dbec4,0x3f55bf0e,
  0xbf673edb,0xbf4e3f18,0x3edb3f67,0x3f183f4e,0x3f62bef1,0x3f46bf22,0xbf623ef1,0xbf463f22,0xbf5c3f04,0xbf3e3f2c,0xbf04bf5c,0xbf2cbf3e,
  0xbec4bf6d,0xbf553f0e,0xbec4bf6d,0xbf553f0e,0x3f3e3f2c,0x3f04bf5c,0x3f2cbf3e,0xbf5cbf04,0xbf75be95,0xbdc93f7f,0x3f753e95,0x3dc9bf7f,
  0x3f7dbe16,0xbeacbf71,0x3e163f7d,0x3f71beac,0xbf6d3ec4,0x3f0e3f55,0xbf6d3ec4,0x3f0e3f55,0x3f2cbf3e,0xbf5cbf04,0xbf3ebf2c,0xbf043f5c,
  0xbe953f75,0x3f7f3dc9,0x3e95bf75,0xbf7fbdc9,0xbe16bf7d,0xbf713eac,0x3f7dbe16,0xbeacbf71,0x3ec43f6d,0xbf0ebf55,0x3ec43f6d,0xbf0ebf55,
  0xbf71beac,0x3f7d3e16,0xbeac3f71,0x3e16bf7d,0x3f62bef1,0xbf463f22,0xbf623ef1,0x3f46bf22,0xbe793f78,0x3d49bf80,0xbf78be79,0x3f803d49,
  0x3f6dbec4,0xbf553f0e,0x3f6dbec4,0xbf553f0e,0xbeac3f71,0x3e16bf7d,0x3f713eac,0xbf7dbe16,0xbef1bf62,0x3f223f46,0x3ef13f62,0xbf22bf46,
  0x3f783e79,0xbf80bd49,0xbe793f78,0x3d49bf80,0xbec4bf6d,0x3f55bf0e,0xbec4bf6d,0x3f55bf0e,0x3f80bd49,0x3e793f78,0xbd49bf80,0x3f78be79,
  0xbe953f75,0xbf7fbdc9,0x3e95bf75,0x3f7f3dc9,0xbf4ebf18,0x3edbbf67,0x3f18bf4e,0x3f673edb,0xbf6d3ec4,0xbf0ebf55,0xbf6d3ec4,0xbf0ebf55,
  0xbd49bf80,0x3f78be79,0xbf803d49,0xbe79bf78,0x3f753e95,0xbdc93f7f,0xbf75be95,0x3dc9bf7f,0xbf183f4e,0xbf67bedb,0xbf4ebf18,0x3edbbf67,
  0x3f80,0x3ec43f6d,0x3f80,0x3ec43f6d,0x3dc93f7f,0x3ef13f62,0x3f7fbdc9,0x3f62bef1,0x3e483f7b,0x3f0e3f55,0xbe48bf7b,0xbf0ebf55,
  0x3e953f75,0x3f223f46,0xbf753e95,0xbf463f22,0x3f808000,0x3f6dbec4,0x3f808000,0x3f6dbec4,0x3f7fbdc9,0x3f62bef1,0xbdc9bf7f,0xbef1bf62,
  0x3f7bbe48,0x3f55bf0e,0xbf7b3e48,0xbf553f0e,0x3f75be95,0x3f46bf22,0x3e953f75,0x3f223f46,0x3f80,0x3f6dbec4,0x3f80,0x3f6dbec4,
  0x3ef13f62,0x3f22bf46,0x3f62bef1,0xbf46bf22,0x3f553f0e,0x3e48bf7b,0xbf55bf0e,0xbe483f7b,0x3f7f3dc9,0xbe95bf75,0xbdc93f7f,0x3f75be95,
  0x3f808000,0xbec4bf6d,0x3f808000,0xbec4bf6d,0x3f62bef1,0xbf46bf22,0xbef1bf62,0xbf223f46,0x3f0ebf55,0xbf7bbe48,0xbf0e3f55,0x3f7b3e48,
  0x3dc9bf7f,0xbf753e95,0x3f7f3dc9,0xbe95bf75,0x3f80,0xbec4bf6d,0x3f80,0xbec4bf6d,0x3f463f22,0xbf75be95,0x3f22bf46,0xbe953f75,
  0x3f7bbe48,0xbf553f0e,0xbf7b3e48,0x3f55bf0e,0x3ef1bf62,0xbdc93f7f,0x3f623ef1,0xbf7fbdc9,0x3f808000,0xbf6d3ec4,0x3f808000,0xbf6d3ec4,
  0x3f22bf46,0xbe953f75,0xbf46bf22,0x3f753e95,0xbe48bf7b,0x3f0e3f55,0x3e483f7b,0xbf0ebf55,0xbf62bef1,0x3f7f3dc9,0x3ef1bf62,0xbdc93f7f,
  0x3f80,0xbf6d3ec4,0x3f80,0xbf6d3ec4,0x3f753e95,0x3dc93f7f,0x3e95bf75,0x3f7fbdc9,0x3f0ebf55,0x3f7b3e48,0xbf0e3f55,0xbf7bbe48,
  0xbf22bf46,0x3ef1bf62,0x3f46bf22,0x3f623ef1,0x3f808000,0x3ec43f6d,0x3f808000,0x3ec43f6d,0x3e95bf75,0x3f7fbdc9,0xbf75be95,0xbdc9bf7f,
  0xbf55bf0e,0x3e48bf7b,0x3f553f0e,0xbe483f7b,0xbf463f22,0xbf62bef1,0xbf22bf46,0x3ef1bf62,0x3f80,0x3ec43f6d,0x3f80,0x3ec43f6d,
  0xbdc9bf7f,0xbef1bf62,0xbf7f3dc9,0xbf623ef1,0x3e483f7b,0x3f0e3f55,0xbe48bf7b,0xbf0ebf55,0xbe95bf75,0xbf22bf46,0x3f75be95,0x3f46bf22,
  0x3f808000,0x3f6dbec4,0x3f808000,0x3f6dbec4,0xbf7f3dc9,0xbf623ef1,0x3dc93f7f,0x3ef13f62,0x3f7bbe48,0x3f55bf0e,0xbf7b3e48,0xbf553f0e,
  0xbf753e95,0xbf463f22,0xbe95bf75,0xbf22bf46,0x3f80,0x3f6dbec4,0x3f80,0x3f6dbec4,0xbef1bf62,0xbf223f46,0xbf623ef1,0x3f463f22,
  0x3f553f0e,0x3e48bf7b,0xbf55bf0e,0xbe483f7b,0xbf7fbdc9,0x3e953f75,0x3dc9bf7f,0xbf753e95,0x3f808000,0xbec4bf6d,0x3f808000,0xbec4bf6d,
  0xbf623ef1,0x3f463f22,0x3ef13f62,0x3f22bf46,0x3f0ebf55,0xbf7bbe48,0xbf0e3f55,0x3f7b3e48,0xbdc93f7f,0x3f75be95,0xbf7fbdc9,0x3e953f75,
  0x3f80,0xbec4bf6d,0x3f80,0xbec4bf6d,0xbf46bf22,0x3f753e95,0xbf223f46,0x3e95bf75,0x3f7bbe48,0xbf553f0e,0xbf7b3e48,0x3f55bf0e,
  0xbef13f62,0x3dc9bf7f,0xbf62bef1,0x3f7f3dc9,0x3f808000,0xbf6d3ec4,0x3f808000,0xbf6d3ec4,0xbf223f46,0x3e95bf75,0x3f463f22,0xbf75be95,
  0xbe48bf7b,0x3f0e3f55,0x3e483f7b,0xbf0ebf55,0x3f623ef1,0xbf7fbdc9,0xbef13f62,0x3dc9bf7f,0x3f80,0xbf6d3ec4,0x3f80,0xbf6d3ec4,
  0xbf75be95,0xbdc9bf7f,0xbe953f75,0xbf7f3dc9,0x3f0ebf55,0x3f7b3e48,0xbf0e3f55,0xbf7bbe48,0x3f223f46,0xbef13f62,0xbf463f22,0xbf62bef1,
  0x3f808000,0x3ec43f6d,0x3f808000,0x3ec43f6d,0xbe953f75,0xbf7f3dc9,0x3f753e95,0x3dc93f7f,0xbf55bf0e,0x3e48bf7b,0x3f553f0e,0xbe483f7b,
  0x3f46bf22,0x3f623ef1,0x3f223f46,0xbef13f62,0x3f353f35,0x3f6d3ec4,0x3f353f35,0x3f6d3ec4,0x3f463f22,0x3f753e95,0x3f22bf46,0x3e95bf75,
  0x3f553f0e,0x3f7b3e48,0xbf55bf0e,0xbf7bbe48,0x3f623ef1,0x3f7f3dc9,0xbef13f62,0xbdc93f7f,0x3f35bf35,0x3ec4bf6d,0x3f35bf35,0x3ec4bf6d,
  0x3f22bf46,0x3e95bf75,0xbf46bf22,0xbf75be95,0x3f0ebf55,0x3e48bf7b,0xbf0e3f55,0xbe483f7b,0x3ef1bf62,0x3dc9bf7f,0x3f623ef1,0x3f7f3dc9,
  0xbf35bf35,0xbec43f6d,0xbf35bf35,0xbec43f6d,0xbf75be95,0x3dc93f7f,0xbe953f75,0x3f7fbdc9,0xbf7b3e48,0x3f0e3f55,0x3f7bbe48,0xbf0ebf55,
  0xbf463f22,0x3f623ef1,0xbf22bf46,0xbef13f62,0xbf353f35,0x3f6d3ec4,0xbf353f35,0x3f6d3ec4,0xbe953f75,0x3f7fbdc9,0x3f753e95,0xbdc9bf7f,
  0x3e483f7b,0x3f55bf0e,0xbe48bf7b,0xbf553f0e,0x3f223f46,0x3ef1bf62,0xbf463f22,0x3f623ef1,0x3f353f35,0xbf6dbec4,0x3f353f35,0xbf6dbec4,
  0x3f7fbdc9,0xbf623ef1,0xbdc9bf7f,0x3ef13f62,0x3f0ebf55,0xbe483f7b,0xbf0e3f55,0x3e48bf7b,0xbe95bf75,0x3f223f46,0x3f75be95,0xbf463f22,
  0x3f35bf35,0xbec43f6d,0x3f35bf35,0xbec43f6d,0xbdc9bf7f,0x3ef13f62,0xbf7f3dc9,0x3f62bef1,0xbf55bf0e,0x3f7b3e48,0x3f553f0e,0xbf7bbe48,
  0xbf753e95,0x3f46bf22,0xbe95bf75,0x3f223f46,0xbf35bf35,0x3ec4bf6d,0xbf35bf35,0x3ec4bf6d,0xbf623ef1,0xbf46bf22,0x3ef13f62,0xbf223f46,
  0x3e483f7b,0xbf553f0e,0xbe48bf7b,0x3f55bf0e,0x3f7f3dc9,0x3e953f75,0xbdc93f7f,0xbf753e95,0xbf353f35,0xbf6dbec4,0xbf353f35,0xbf6dbec4,
  0x3ef13f62,0xbf223f46,0x3f62bef1,0x3f463f22,0x3f7bbe48,0x3f0e3f55,0xbf7b3e48,0xbf0ebf55,0x3dc9bf7f,0x3f75be95,0x3f7f3dc9,0x3e953f75,
  0x3f353f35,0x3f6d3ec4,0x3f353f35,0x3f6d3ec4,0xbf46bf22,0xbf75be95,0xbf223f46,0xbe953f75,0x3f553f0e,0x3f7b3e48,0xbf55bf0e,0xbf7bbe48,
  0xbf62bef1,0xbf7fbdc9,0x3ef1bf62,0x3dc9bf7f,0x3f35bf35,0x3ec4bf6d,0x3f35bf35,0x3ec4bf6d,0xbf223f46,0xbe953f75,0x3f463f22,0x3f753e95,
  0x3f0ebf55,0x3e48bf7b,0xbf0e3f55,0xbe483f7b,0xbef13f62,0xbdc93f7f,0xbf62bef1,0xbf7fbdc9,0xbf35bf35,0xbec43f6d,0xbf35bf35,0xbec43f6d,
  0x3f753e95,0xbdc9bf7f,0x3e95bf75,0xbf7f3dc9,0xbf7b3e48,0x3f0e3f55,0x3f7bbe48,0xbf0ebf55,0x3f46bf22,0xbf62bef1,0x3f223f46,0x3ef1bf62,
  0xbf353f35,0x3f6d3ec4,0xbf353f35,0x3f6d3ec4,0x3e95bf75,0xbf7f3dc9,0xbf75be95,0x3dc93f7f,0x3e483f7b,0x3f55bf0e,0xbe48bf7b,0xbf553f0e,
  0xbf22bf46,0xbef13f62,0x3f46bf22,0xbf62bef1,0x3f353f35,0xbf6dbec4,0x3f353f35,0xbf6dbec4,0xbf7f3dc9,0x3f62bef1,0x3dc93f7f,0xbef1bf62,
  0x3f0ebf55,0xbe483f7b,0xbf0e3f55,0x3e48bf7b,0x3e953f75,0xbf22bf46,0xbf753e95,0x3f46bf22,0x3f35bf35,0xbec43f6d,0x3f35bf35,0xbec43f6d,
  0x3dc93f7f,0xbef1bf62,0x3f7fbdc9,0xbf623ef1,0xbf55bf0e,0x3f7b3e48,0x3f553f0e,0xbf7bbe48,0x3f75be95,0xbf463f22,0x3e953f75,0xbf22bf46,
  0xbf35bf35,0x3ec4bf6d,0xbf35bf35,0x3ec4bf6d,0x3f62bef1,0x3f463f22,0xbef1bf62,0x3f22bf46,0x3e483f7b,0xbf553f0e,0xbe48bf7b,0x3f55bf0e,
  0xbf7fbdc9,0xbe95bf75,0x3dc9bf7f,0x3f75be95,0xbf353f35,0xbf6dbec4,0xbf353f35,0xbf6dbec4,0xbef1bf62,0x3f22bf46,0xbf623ef1,0xbf46bf22,
  0x3f7bbe48,0x3f0e3f55,0xbf7b3e48,0xbf0ebf55,0xbdc93f7f,0xbf753e95,0xbf7fbdc9,0xbe95bf75,0x3f80,0x3f0e3f55,0x3f80,0x3f0e3f55,
  0x3e163f7d,0x3f2c3f3e,0x3f7dbe16,0x3f3ebf2c,0x3e953f75,0x3f463f22,0xbe95bf75,0xbf46bf22,0x3edb3f67,0x3f5c3f04,0xbf673edb,0xbf043f5c,
  0x3f808000,0x3f55bf0e,0x3f808000,0x3f55bf0e,0x3f7dbe16,0x3f3ebf2c,0xbe16bf7d,0xbf2cbf3e,0x3f75be95,0x3f22bf46,0xbf753e95,0xbf223f46,
  0x3f67bedb,0x3f04bf5c,0x3edb3f67,0x3f5c3f04,0x3f80,0x3f55bf0e,0x3f80,0x3f55bf0e,0x3f043f5c,0x3edbbf67,0x3f5cbf04,0xbf67bedb,
  0x3f623ef1,0xbdc9bf7f,0xbf62bef1,0x3dc93f7f,0x3f80bd49,0xbf18bf4e,0x3d493f80,0x3f4ebf18,0x3f808000,0xbf0ebf55,0x3f808000,0xbf0ebf55,
  0x3f5cbf04,0xbf67bedb,0xbf04bf5c,0xbedb3f67,0x3ef1bf62,0xbf7f3dc9,0xbef13f62,0x3f7fbdc9,0xbd49bf80,0xbf4e3f18,0x3f80bd49,0xbf18bf4e,
  0x3f80,0xbf0ebf55,0x3f80,0xbf0ebf55,0x3f4e3f18,0xbf80bd49,0x3f18bf4e,0xbd493f80,0x3f75be95,0xbf223f46,0xbf753e95,0x3f22bf46,
  0x3eacbf71,0x3e793f78,0x3f713eac,0xbf783e79,0x3f808000,0xbf553f0e,0x3f808000,0xbf553f0e,0x3f18bf4e,0xbd493f80,0xbf4ebf18,0x3f803d49,
  0xbe95bf75,0x3f463f22,0x3e953f75,0xbf46bf22,0xbf71beac,0x3f78be79,0x3eacbf71,0x3e793f78,0x3f80,0xbf553f0e,0x3f80,0xbf553f0e,
  0x3f783e79,0x3eac3f71,0x3e79bf78,0x3f71beac,0x3ef1bf62,0x3f7fbdc9,0xbef13f62,0xbf7f3dc9,0xbf3ebf2c,0x3e16bf7d,0x3f2cbf3e,0x3f7d3e16,
  0x3f808000,0x3f0e3f55,0x3f808000,0x3f0e3f55,0x3e79bf78,0x3f71beac,0xbf78be79,0xbeacbf71,0xbf62bef1,0xbdc9bf7f,0x3f623ef1,0x3dc93f7f,
  0xbf2c3f3e,0xbf7dbe16,0xbf3ebf2c,0x3e16bf7d,0x3f80,0x3f0e3f55,0x3f80,0x3f0e3f55,0xbe16bf7d,0xbf2cbf3e,0xbf7d3e16,0xbf3e3f2c,
  0x3e953f75,0x3f463f22,0xbe95bf75,0xbf46bf22,0xbedbbf67,0xbf5cbf04,0x3f67bedb,0x3f04bf5c,0x3f808000,0x3f55bf0e,0x3f808000,0x3f55bf0e,
  0xbf7d3e16,0xbf3e3f2c,0x3e163f7d,0x3f2c3f3e,0x3f75be95,0x3f22bf46,0xbf753e95,0xbf223f46,0xbf673edb,0xbf043f5c,0xbedbbf67,0xbf5cbf04,
  0x3f80,0x3f55bf0e,0x3f80,0x3f55bf0e,0xbf04bf5c,0xbedb3f67,0xbf5c3f04,0x3f673edb,0x3f623ef1,0xbdc9bf7f,0xbf62bef1,0x3dc93f7f,
  0xbf803d49,0x3f183f4e,0xbd49bf80,0xbf4e3f18,0x3f808000,0xbf0ebf55,0x3f808000,0xbf0ebf55,0xbf5c3f04,0x3f673edb,0x3f043f5c,0x3edbbf67,
  0x3ef1bf62,0xbf7f3dc9,0xbef13f62,0x3f7fbdc9,0x3d493f80,0x3f4ebf18,0xbf803d49,0x3f183f4e,0x3f80,0xbf0ebf55,0x3f80,0xbf0ebf55,
  0xbf4ebf18,0x3f803d49,0xbf183f4e,0x3d49bf80,0x3f75be95,0xbf223f46,0xbf753e95,0x3f22bf46,0xbeac3f71,0xbe79bf78,0xbf71beac,0x3f78be79,
  0x3f808000,0xbf553f0e,0x3f808000,0xbf553f0e,0xbf183f4e,0x3d49bf80,0x3f4e3f18,0xbf80bd49,0xbe95bf75,0x3f463f22,0x3e953f75,0xbf46bf22,
  0x3f713eac,0xbf783e79,0xbeac3f71,0xbe79bf78,0x3f80,0xbf553f0e,0x3f80,0xbf553f0e,0xbf78be79,0xbeacbf71,0xbe793f78,0xbf713eac,
  0x3ef1bf62,0x3f7fbdc9,0xbef13f62,0xbf7f3dc9,0x3f3e3f2c,0xbe163f7d,0xbf2c3f3e,0xbf7dbe16,0x3f808000,0x3f0e3f55,0x3f808000,0x3f0e3f55,
  0xbe793f78,0xbf713eac,0x3f783e79,0x3eac3f71,0xbf62bef1,0xbdc9bf7f,0x3f623ef1,0x3dc93f7f,0x3f2cbf3e,0x3f7d3e16,0x3f3e3f2c,0xbe163f7d,
  0x3f6d3ec4,0x3f7bbe48,0x3f6d3ec4,0x3f7bbe48,0x3f783e79,0x3f71beac,0x3e79bf78,0xbeacbf71,0x3f7f3dc9,0x3f62bef1,0xbf7fbdc9,0xbf623ef1,
  0x3f80bd49,0x3f4ebf18,0x3d493f80,0x3f183f4e,0x3ec4bf6d,0xbe48bf7b,0x3ec4bf6d,0xbe48bf7b,0x3e79bf78,0xbeacbf71,0xbf78be79,0xbf713eac,
  0x3dc9bf7f,0xbef1bf62,0xbdc93f7f,0x3ef13f62,0xbd49bf80,0xbf18bf4e,0x3f80bd49,0x3f4ebf18,0xbf6dbec4,0x3e483f7b,0xbf6dbec4,0x3e483f7b,
  0xbf7d3e16,0x3f2c3f3e,0x3e163f7d,0x3f3ebf2c,0xbf463f22,0x3f753e95,0x3f46bf22,0xbf75be95,0xbeac3f71,0x3f78be79,0xbf71beac,0x3e793f78,
  0xbec43f6d,0x3f7bbe48,0xbec43f6d,0x3f7bbe48,0x3e163f7d,0x3f3ebf2c,0x3f7dbe16,0xbf2cbf3e,0x3f223f46,0x3e95bf75,0xbf22bf46,0xbe953f75,
  0x3f713eac,0xbe79bf78,0xbeac3f71,0x3f78be79,0x3f6d3ec4,0xbf7b3e48,0x3f6d3ec4,0xbf7b3e48,0x3f5cbf04,0xbedb3f67,0xbf04bf5c,0x3f673edb,
  0x3dc9bf7f,0x3ef13f62,0xbdc93f7f,0xbef1bf62,0xbf3ebf2c,0x3f7d3e16,0x3f2cbf3e,0xbe163f7d,0x3ec4bf6d,0x3e483f7b,0x3ec4bf6d,0x3e483f7b,
  0xbf04bf5c,0x3f673edb,0xbf5c3f04,0x3edbbf67,0xbf7fbdc9,0x3f62bef1,0x3f7f3dc9,0xbf623ef1,0xbf2c3f3e,0x3e16bf7d,0xbf3ebf2c,0x3f7d3e16,
  0xbf6dbec4,0xbe48bf7b,0xbf6dbec4,0xbe48bf7b,0xbf183f4e,0xbf80bd49,0x3f4e3f18,0xbd493f80,0x3f223f46,0xbe953f75,0xbf22bf46,0x3e95bf75,
  0x3f67bedb,0x3f5c3f04,0x3edb3f67,0xbf043f5c,0xbec43f6d,0xbf7b3e48,0xbec43f6d,0xbf7b3e48,0x3f4e3f18,0xbd493f80,0x3f18bf4e,0x3f803d49,
  0x3f46bf22,0x3f753e95,0xbf463f22,0xbf75be95,0xbedbbf67,0x3f04bf5c,0x3f67bedb,0x3f5c3f04,0x3f6d3ec4,0x3f7bbe48,0x3f6d3ec4,0x3f7bbe48,
  0xbf78be79,0xbf713eac,0xbe793f78,0x3eac3f71,0x3f7f3dc9,0x3f62bef1,0xbf7fbdc9,0xbf623ef1,0xbf803d49,0xbf4e3f18,0xbd49bf80,0xbf18bf4e,
  0x3ec4bf6d,0xbe48bf7b,0x3ec4bf6d,0xbe48bf7b,0xbe793f78,0x3eac3f71,0x3f783e79,0x3f71beac,0x3dc9bf7f,0xbef1bf62,0xbdc93f7f,0x3ef13f62,
  0x3d493f80,0x3f183f4e,0xbf803d49,0xbf4e3f18,0xbf6dbec4,0x3e483f7b,0xbf6dbec4,0x3e483f7b,0x3f7dbe16,0xbf2cbf3e,0xbe16bf7d,0xbf3e3f2c,
  0xbf463f22,0x3f753e95,0x3f46bf22,0xbf75be95,0x3eacbf71,0xbf783e79,0x3f713eac,0xbe79bf78,0xbec43f6d,0x3f7bbe48,0xbec43f6d,0x3f7bbe48,
  0xbe16bf7d,0xbf3e3f2c,0xbf7d3e16,0x3f2c3f3e,0x3f223f46,0x3e95bf75,0xbf22bf46,0xbe953f75,0xbf71beac,0x3e793f78,0x3eacbf71,0xbf783e79,
  0x3f6d3ec4,0xbf7b3e48,0x3f6d3ec4,0xbf7b3e48,0xbf5c3f04,0x3edbbf67,0x3f043f5c,0xbf67bedb,0x3dc9bf7f,0x3ef13f62,0xbdc93f7f,0xbef1bf62,
  0x3f3e3f2c,0xbf7dbe16,0xbf2c3f3e,0x3e16bf7d,0x3ec4bf6d,0x3e483f7b,0x3ec4bf6d,0x3e483f7b,0x3f043f5c,0xbf67bedb,0x3f5cbf04,0xbedb3f67,
  0xbf7fbdc9,0x3f62bef1,0x3f7f3dc9,0xbf623ef1,0x3f2cbf3e,0xbe163f7d,0x3f3e3f2c,0xbf7dbe16,0xbf6dbec4,0xbe48bf7b,0xbf6dbec4,0xbe48bf7b,
  0x3f18bf4e,0x3f803d49,0xbf4ebf18,0x3d49bf80,0x3f223f46,0xbe953f75,0xbf22bf46,0x3e95bf75,0xbf673edb,0xbf5cbf04,0xbedbbf67,0x3f04bf5c,
  0xbec43f6d,0xbf7b3e48,0xbec43f6d,0xbf7b3e48,0xbf4ebf18,0x3d49bf80,0xbf183f4e,0xbf80bd49,0x3f46bf22,0x3f753e95,0xbf463f22,0xbf75be95,
  0x3edb3f67,0xbf043f5c,0xbf673edb,0xbf5cbf04,0x3f80,0x3f353f35,0x3f80,0x3f353f35,0x3e483f7b,0x3f553f0e,0x3f7bbe48,0x3f0ebf55,
  0x3ec43f6d,0x3f6d3ec4,0xbec4bf6d,0xbf6dbec4,0x3f0e3f55,0x3f7b3e48,0xbf553f0e,0xbe483f7b,0x3f808000,0x3f35bf35,0x3f808000,0x3f35bf35,
  0x3f7bbe48,0x3f0ebf55,0xbe48bf7b,0xbf55bf0e,0x3f6dbec4,0x3ec4bf6d,0xbf6d3ec4,0xbec43f6d,0x3f55bf0e,0x3e48bf7b,0x3f0e3f55,0x3f7b3e48,
  0x3f80,0x3f35bf35,0x3f80,0x3f35bf35,0x3f0e3f55,0x3e48bf7b,0x3f55bf0e,0xbf7bbe48,0x3f6d3ec4,0xbec4bf6d,0xbf6dbec4,0x3ec43f6d,
  0x3f7bbe48,0xbf55bf0e,0x3e483f7b,0x3f0ebf55,0x3f808000,0xbf35bf35,0x3f808000,0xbf35bf35,0x3f55bf0e,0xbf7bbe48,0xbf0ebf55,0xbe483f7b,
  0x3ec4bf6d,0xbf6d3ec4,0xbec43f6d,0x3f6dbec4,0xbe48bf7b,0xbf0e3f55,0x3f7bbe48,0xbf55bf0e,0x3f80,0xbf35bf35,0x3f80,0xbf35bf35,
  0x3f553f0e,0xbf7b3e48,0x3f0ebf55,0x3e483f7b,0x3f6dbec4,0xbec43f6d,0xbf6d3ec4,0x3ec4bf6d,0x3e48bf7b,0x3f0e3f55,0x3f7b3e48,0xbf553f0e,
  0x3f808000,0xbf353f35,0x3f808000,0xbf353f35,0x3f0ebf55,0x3e483f7b,0xbf55bf0e,0x3f7bbe48,0xbec4bf6d,0x3f6d3ec4,0x3ec43f6d,0xbf6dbec4,
  0xbf7bbe48,0x3f55bf0e,0x3e48bf7b,0x3f0e3f55,0x3f80,0xbf353f35,0x3f80,0xbf353f35,0x3f7b3e48,0x3f0e3f55,0x3e48bf7b,0x3f55bf0e,
  0x3ec4bf6d,0x3f6dbec4,0xbec43f6d,0xbf6d3ec4,0xbf55bf0e,0xbe48bf7b,0x3f0ebf55,0x3f7bbe48,0x3f808000,0x3f353f35,0x3f808000,0x3f353f35,
  0x3e48bf7b,0x3f55bf0e,0xbf7bbe48,0xbf0ebf55,0xbf6dbec4,0xbec4bf6d,0x3f6d3ec4,0x3ec43f6d,0xbf0e3f55,0xbf7b3e48,0xbf55bf0e,0xbe48bf7b,
  0x3f80,0x3f353f35,0x3f80,0x3f353f35,0xbe48bf7b,0xbf55bf0e,0xbf7b3e48,0xbf0e3f55,0x3ec43f6d,0x3f6d3ec4,0xbec4bf6d,0xbf6dbec4,
  0xbf0ebf55,0xbf7bbe48,0x3f55bf0e,0x3e48bf7b,0x3f808000,0x3f35bf35,0x3f808000,0x3f35bf35,0xbf7b3e48,0xbf0e3f55,0x3e483f7b,0x3f553f0e,
  0x3f6dbec4,0x3ec4bf6d,0xbf6d3ec4,0xbec43f6d,0xbf553f0e,0xbe483f7b,0xbf0ebf55,0xbf7bbe48,0x3f80,0x3f35bf35,0x3f80,0x3f35bf35,
  0xbf0ebf55,0xbe483f7b,0xbf553f0e,0x3f7b3e48,0x3f6d3ec4,0xbec4bf6d,0xbf6dbec4,0x3ec43f6d,0xbf7b3e48,0x3f553f0e,0xbe48bf7b,0xbf0e3f55,
  0x3f808000,0xbf35bf35,0x3f808000,0xbf35bf35,0xbf553f0e,0x3f7b3e48,0x3f0e3f55,0x3e48bf7b,0x3ec4bf6d,0xbf6d3ec4,0xbec43f6d,0x3f6dbec4,
  0x3e483f7b,0x3f0ebf55,0xbf7b3e48,0x3f553f0e,0x3f80,0xbf35bf35,0x3f80,0xbf35bf35,0xbf55bf0e,0x3f7bbe48,0xbf0e3f55,0xbe48bf7b,
  0x3f6dbec4,0xbec43f6d,0xbf6d3ec4,0x3ec4bf6d,0xbe483f7b,0xbf0ebf55,0xbf7bbe48,0x3f55bf0e,0x3f808000,0xbf353f35,0x3f808000,0xbf353f35,
  0xbf0e3f55,0xbe48bf7b,0x3f553f0e,0xbf7b3e48,0xbec4bf6d,0x3f6d3ec4,0x3ec43f6d,0xbf6dbec4,0x3f7b3e48,0xbf553f0e,0xbe483f7b,0xbf0ebf55,
  0x3f80,0xbf353f35,0x3f80,0xbf353f35,0xbf7bbe48,0xbf0ebf55,0xbe483f7b,0xbf553f0e,0x3ec4bf6d,0x3f6dbec4,0xbec43f6d,0xbf6d3ec4,
  0x3f553f0e,0x3e483f7b,0xbf0e3f55,0xbf7b3e48,0x3f808000,0x3f353f35,0x3f808000,0x3f353f35,0xbe483f7b,0xbf553f0e,0x3f7b3e48,0x3f0e3f55,
  0xbf6dbec4,0xbec4bf6d,0x3f6d3ec4,0x3ec43f6d,0x3f0ebf55,0x3f7bbe48,0x3f553f0e,0x3e483f7b,0x3f800000,0x3f35bf35,0x3f800000,0x3f35bf35,
  0x3f7bbe48,0x3f0ebf55,0xbe48bf7b,0xbf55bf0e,0x3f6dbec4,0x3ec4bf6d,0xbf6d3ec4,0xbec43f6d,0x3f55bf0e,0x3e48bf7b,0x3f0e3f55,0x3f7b3e48,
  0xbf80,0xbf35bf35,0xbf80,0xbf35bf35,0xbe48bf7b,0xbf55bf0e,0xbf7b3e48,0xbf0e3f55,0xbec4bf6d,0xbf6dbec4,0x3ec43f6d,0x3f6d3ec4,
  0xbf0ebf55,0xbf7bbe48,0x3f55bf0e,0x3e48bf7b,0xbf800000,0x3f353f35,0xbf800000,0x3f353f35,0xbf553f0e,0x3f7b3e48,0x3f0e3f55,0x3e48bf7b,
  0xbec43f6d,0x3f6dbec4,0x3ec4bf6d,0xbf6d3ec4,0x3e483f7b,0x3f0ebf55,0xbf7b3e48,0x3f553f0e,0x3f80,0x3f35bf35,0x3f80,0x3f35bf35,
  0x3f0e3f55,0x3e48bf7b,0x3f55bf0e,0xbf7bbe48,0x3f6d3ec4,0xbec4bf6d,0xbf6dbec4,0x3ec43f6d,0x3f7bbe48,0xbf55bf0e,0x3e483f7b,0x3f0ebf55,
  0x3f800000,0xbf353f35,0x3f800000,0xbf353f35,0x3f0ebf55,0x3e483f7b,0xbf55bf0e,0x3f7bbe48,0xbec4bf6d,0x3f6d3ec4,0x3ec43f6d,0xbf6dbec4,
  0xbf7bbe48,0x3f55bf0e,0x3e48bf7b,0x3f0e3f55,0xbf80,0x3f353f35,0xbf80,0x3f353f35,0xbf55bf0e,0x3f7bbe48,0xbf0e3f55,0xbe48bf7b,
  0xbf6d3ec4,0x3ec4bf6d,0x3f6dbec4,0xbec43f6d,0xbe483f7b,0xbf0ebf55,0xbf7bbe48,0x3f55bf0e,0xbf800000,0xbf35bf35,0xbf800000,0xbf35bf35,
  0xbe483f7b,0xbf553f0e,0x3f7b3e48,0x3f0e3f55,0x3f6d3ec4,0x3ec43f6d,0xbf6dbec4,0xbec4bf6d,0x3f0ebf55,0x3f7bbe48,0x3f553f0e,0x3e483f7b,
  0x3f80,0xbf353f35,0x3f80,0xbf353f35,0x3f7b3e48,0x3f0e3f55,0x3e48bf7b,0x3f55bf0e,0x3ec4bf6d,0x3f6dbec4,0xbec43f6d,0xbf6d3ec4,
  0xbf55bf0e,0xbe48bf7b,0x3f0ebf55,0x3f7bbe48,0x3f800000,0x3f35bf35,0x3f800000,0x3f35bf35,0xbf7b3e48,0xbf0e3f55,0x3e483f7b,0x3f553f0e,
  0x3f6dbec4,0x3ec4bf6d,0xbf6d3ec4,0xbec43f6d,0xbf553f0e,0xbe483f7b,0xbf0ebf55,0xbf7bbe48,0xbf80,0xbf35bf35,0xbf80,0xbf35bf35,
  0x3e483f7b,0x3f553f0e,0x3f7bbe48,0x3f0ebf55,0xbec4bf6d,0xbf6dbec4,0x3ec43f6d,0x3f6d3ec4,0x3f0e3f55,0x3f7b3e48,0xbf553f0e,0xbe483f7b,
  0xbf800000,0x3f353f35,0xbf800000,0x3f353f35,0x3f55bf0e,0xbf7bbe48,0xbf0ebf55,0xbe483f7b,0xbec43f6d,0x3f6dbec4,0x3ec4bf6d,0xbf6d3ec4,
  0xbe48bf7b,0xbf0e3f55,0x3f7bbe48,0xbf55bf0e,0x3f80,0x3f35bf35,0x3f80,0x3f35bf35,0xbf0ebf55,0xbe483f7b,0xbf553f0e,0x3f7b3e48,
  0x3f6d3ec4,0xbec4bf6d,0xbf6dbec4,0x3ec43f6d,0xbf7b3e48,0x3f553f0e,0xbe48bf7b,0xbf0e3f55,0x3f800000,0xbf353f35,0x3f800000,0xbf353f35,
  0xbf0e3f55,0xbe48bf7b,0x3f553f0e,0xbf7b3e48,0xbec4bf6d,0x3f6d3ec4,0x3ec43f6d,0xbf6dbec4,0x3f7b3e48,0xbf553f0e,0xbe483f7b,0xbf0ebf55,
  0xbf80,0x3f353f35,0xbf80,0x3f353f35,0x3f553f0e,0xbf7b3e48,0x3f0ebf55,0x3e483f7b,0xbf6d3ec4,0x3ec4bf6d,0x3f6dbec4,0xbec43f6d,
  0x3e48bf7b,0x3f0e3f55,0x3f7b3e48,0xbf553f0e,0xbf800000,0xbf35bf35,0xbf800000,0xbf35bf35,0x3e48bf7b,0x3f55bf0e,0xbf7bbe48,0xbf0ebf55,
  0x3f6d3ec4,0x3ec43f6d,0xbf6dbec4,0xbec4bf6d,0xbf0e3f55,0xbf7b3e48,0xbf55bf0e,0xbe48bf7b,0x3f80,0xbf353f35,0x3f80,0xbf353f35,
  0xbf7bbe48,0xbf0ebf55,0xbe483f7b,0xbf553f0e,0x3ec4bf6d,0x3f6dbec4,0xbec43f6d,0xbf6d3ec4,0x3f553f0e,0x3e483f7b,0xbf0e3f55,0xbf7b3e48,
  0x3f80,0x3f553f0e,0x3f80,0x3f553f0e,0x3e793f78,0x3f713eac,0x3f78be79,0x3eacbf71,0x3ef13f62,0x3f7f3dc9,0xbef1bf62,0xbf7fbdc9,
  0x3f2c3f3e,0x3f7dbe16,0xbf3e3f2c,0x3e163f7d,0x3f808000,0x3f0ebf55,0x3f808000,0x3f0ebf55,0x3f78be79,0x3eacbf71,0xbe79bf78,0xbf71beac,
  0x3f62bef1,0x3dc9bf7f,0xbf623ef1,0xbdc93f7f,0x3f3ebf2c,0xbe16bf7d,0x3f2c3f3e,0x3f7dbe16,0x3f80,0x3f0ebf55,0x3f80,0x3f0ebf55,
  0x3f183f4e,0xbd49bf80,0x3f4ebf18,0xbf803d49,0x3f753e95,0xbf22bf46,0xbf75be95,0x3f223f46,0x3f71beac,0xbf78be79,0x3eac3f71,0x3e79bf78,
  0x3f808000,0xbf55bf0e,0x3f808000,0xbf55bf0e,0x3f4ebf18,0xbf803d49,0xbf18bf4e,0x3d493f80,0x3e95bf75,0xbf463f22,0xbe953f75,0x3f46bf22,
  0xbeacbf71,0xbe793f78,0x3f71beac,0xbf78be79,0x3f80,0xbf55bf0e,0x3f80,0xbf55bf0e,0x3f5c3f04,0xbf673edb,0x3f04bf5c,0x3edb3f67,
  0x3f62bef1,0xbdc93f7f,0xbf623ef1,0x3dc9bf7f,0x3d49bf80,0x3f4e3f18,0x3f803d49,0xbf183f4e,0x3f808000,0xbf0e3f55,0x3f808000,0xbf0e3f55,
  0x3f04bf5c,0x3edb3f67,0xbf5cbf04,0x3f67bedb,0xbef1bf62,0x3f7f3dc9,0x3ef13f62,0xbf7fbdc9,0xbf80bd49,0x3f18bf4e,0x3d49bf80,0x3f4e3f18,
  0x3f80,0xbf0e3f55,0x3f80,0xbf0e3f55,0x3f7d3e16,0x3f3e3f2c,0x3e16bf7d,0x3f2cbf3e,0x3e95bf75,0x3f46bf22,0xbe953f75,0xbf463f22,
  0xbf67bedb,0xbf04bf5c,0x3edbbf67,0x3f5cbf04,0x3f808000,0x3f553f0e,0x3f808000,0x3f553f0e,0x3e16bf7d,0x3f2cbf3e,0xbf7dbe16,0xbf3ebf2c,
  0xbf75be95,0xbf22bf46,0x3f753e95,0x3f223f46,0xbedb3f67,0xbf5c3f04,0xbf67bedb,0xbf04bf5c,0x3f80,0x3f553f0e,0x3f80,0x3f553f0e,
  0xbe79bf78,0xbf71beac,0xbf783e79,0xbeac3f71,0x3ef13f62,0x3f7f3dc9,0xbef1bf62,0xbf7fbdc9,0xbf2cbf3e,0xbf7d3e16,0x3f3ebf2c,0xbe16bf7d,
  0x3f808000,0x3f0ebf55,0x3f808000,0x3f0ebf55,0xbf783e79,0xbeac3f71,0x3e793f78,0x3f713eac,0x3f62bef1,0x3dc9bf7f,0xbf623ef1,0xbdc93f7f,
  0xbf3e3f2c,0x3e163f7d,0xbf2cbf3e,0xbf7d3e16,0x3f80,0x3f0ebf55,0x3f80,0x3f0ebf55,0xbf18bf4e,0x3d493f80,0xbf4e3f18,0x3f80bd49,
  0x3f753e95,0xbf22bf46,0xbf75be95,0x3f223f46,0xbf713eac,0x3f783e79,0xbeacbf71,0xbe793f78,0x3f808000,0xbf55bf0e,0x3f808000,0xbf55bf0e,
  0xbf4e3f18,0x3f80bd49,0x3f183f4e,0xbd49bf80,0x3e95bf75,0xbf463f22,0xbe953f75,0x3f46bf22,0x3eac3f71,0x3e79bf78,0xbf713eac,0x3f783e79,
  0x3f80,0xbf55bf0e,0x3f80,0xbf55bf0e,0xbf5cbf04,0x3f67bedb,0xbf043f5c,0xbedbbf67,0x3f62bef1,0xbdc93f7f,0xbf623ef1,0x3dc9bf7f,
  0xbd493f80,0xbf4ebf18,0xbf80bd49,0x3f18bf4e,0x3f808000,0xbf0e3f55,0x3f808000,0xbf0e3f55,0xbf043f5c,0xbedbbf67,0x3f5c3f04,0xbf673edb,
  0xbef1bf62,0x3f7f3dc9,0x3ef13f62,0xbf7fbdc9,0x3f803d49,0xbf183f4e,0xbd493f80,0xbf4ebf18,0x3f80,0xbf0e3f55,0x3f80,0xbf0e3f55,
  0xbf7dbe16,0xbf3ebf2c,0xbe163f7d,0xbf2c3f3e,0x3e95bf75,0x3f46bf22,0xbe953f75,0xbf463f22,0x3f673edb,0x3f043f5c,0xbedb3f67,0xbf5c3f04,
  0x3f808000,0x3f553f0e,0x3f808000,0x3f553f0e,0xbe163f7d,0xbf2c3f3e,0x3f7d3e16,0x3f3e3f2c,0xbf75be95,0xbf22bf46,0x3f753e95,0x3f223f46,
  0x3edbbf67,0x3f5cbf04,0x3f673edb,0x3f043f5c,0x3f6dbec4,0x3e48bf7b,0x3f6dbec4,0x3e48bf7b,0x3f4ebf18,0xbd49bf80,0xbf18bf4e,0xbf803d49,
  0x3f22bf46,0xbe95bf75,0xbf223f46,0x3e953f75,0x3edbbf67,0xbf04bf5c,0x3f673edb,0x3f5cbf04,0xbec4bf6d,0xbf7bbe48,0xbec4bf6d,0xbf7bbe48,
  0xbf18bf4e,0xbf803d49,0xbf4e3f18,0x3d493f80,0xbf46bf22,0xbf753e95,0x3f463f22,0x3f75be95,0xbf67bedb,0xbf5c3f04,0x3edbbf67,0xbf04bf5c,
  0xbf6d3ec4,0x3f7b3e48,0xbf6d3ec4,0x3f7b3e48,0xbf043f5c,0x3f67bedb,0x3f5c3f04,0xbedbbf67,0x3dc93f7f,0x3ef1bf62,0xbdc9bf7f,0xbef13f62,
  0x3f2c3f3e,0xbe16bf7d,0xbf3e3f2c,0x3f7dbe16,0x3ec43f6d,0x3e48bf7b,0x3ec43f6d,0x3e48bf7b,0x3f5c3f04,0xbedbbf67,0x3f04bf5c,0xbf673edb,
  0x3f7fbdc9,0xbf62bef1,0xbf7f3dc9,0x3f623ef1,0x3f3ebf2c,0xbf7d3e16,0x3f2c3f3e,0xbe16bf7d,0x3f6dbec4,0xbe483f7b,0x3f6dbec4,0xbe483f7b,
  0x3e16bf7d,0x3f3e3f2c,0xbf7dbe16,0x3f2cbf3e,0xbf46bf22,0x3f75be95,0x3f463f22,0xbf753e95,0xbf713eac,0x3e79bf78,0xbeacbf71,0x3f783e79,
  0xbec4bf6d,0x3f7b3e48,0xbec4bf6d,0x3f7b3e48,0xbf7dbe16,0x3f2cbf3e,0xbe163f7d,0xbf3ebf2c,0xbf223f46,0xbe95bf75,0x3f22bf46,0x3e953f75,
  0x3eac3f71,0xbf78be79,0xbf713eac,0x3e79bf78,0xbf6d3ec4,0xbf7bbe48,0xbf6d3ec4,0xbf7bbe48,0x3e793f78,0xbeac3f71,0x3f78be79,0x3f713eac,
  0x3f7fbdc9,0x3f623ef1,0xbf7f3dc9,0xbf62bef1,0x3d49bf80,0x3f18bf4e,0x3f803d49,0x3f4e3f18,0x3ec43f6d,0xbe483f7b,0x3ec43f6d,0xbe483f7b,
  0x3f78be79,0x3f713eac,0xbe79bf78,0x3eacbf71,0xbdc9bf7f,0x3ef1bf62,0x3dc93f7f,0xbef13f62,0xbf80bd49,0xbf4ebf18,0x3d49bf80,0x3f18bf4e,
  0x3f6dbec4,0x3e48bf7b,0x3f6dbec4,0x3e48bf7b,0xbf4e3f18,0x3d493f80,0x3f183f4e,0x3f80bd49,0x3f22bf46,0xbe95bf75,0xbf223f46,0x3e953f75,
  0xbedb3f67,0x3f043f5c,0xbf67bedb,0xbf5c3f04,0xbec4bf6d,0xbf7bbe48,0xbec4bf6d,0xbf7bbe48,0x3f183f4e,0x3f80bd49,0x3f4ebf18,0xbd49bf80,
  0xbf46bf22,0xbf753e95,0x3f463f22,0x3f75be95,0x3f673edb,0x3f5cbf04,0xbedb3f67,0x3f043f5c,0xbf6d3ec4,0x3f7b3e48,0xbf6d3ec4,0x3f7b3e48,
  0x3f04bf5c,0xbf673edb,0xbf5cbf04,0x3edb3f67,0x3dc93f7f,0x3ef1bf62,0xbdc9bf7f,0xbef13f62,0xbf2cbf3e,0x3e163f7d,0x3f3ebf2c,0xbf7d3e16,
  0x3ec43f6d,0x3e48bf7b,0x3ec43f6d,0x3e48bf7b,0xbf5cbf04,0x3edb3f67,0xbf043f5c,0x3f67bedb,0x3f7fbdc9,0xbf62bef1,0xbf7f3dc9,0x3f623ef1,
  0xbf3e3f2c,0x3f7dbe16,0xbf2cbf3e,0x3e163f7d,0x3f6dbec4,0xbe483f7b,0x3f6dbec4,0xbe483f7b,0xbe163f7d,0xbf3ebf2c,0x3f7d3e16,0xbf2c3f3e,
  0xbf46bf22,0x3f75be95,0x3f463f22,0xbf753e95,0x3f71beac,0xbe793f78,0x3eac3f71,0xbf78be79,0xbec4bf6d,0x3f7b3e48,0xbec4bf6d,0x3f7b3e48,
  0x3f7d3e16,0xbf2c3f3e,0x3e16bf7d,0x3f3e3f2c,0xbf223f46,0xbe95bf75,0x3f22bf46,0x3e953f75,0xbeacbf71,0x3f783e79,0x3f71beac,0xbe793f78,
  0xbf6d3ec4,0xbf7bbe48,0xbf6d3ec4,0xbf7bbe48,0xbe79bf78,0x3eacbf71,0xbf783e79,0xbf71beac,0x3f7fbdc9,0x3f623ef1,0xbf7f3dc9,0xbf62bef1,
  0xbd493f80,0xbf183f4e,0xbf80bd49,0xbf4ebf18,0x3ec43f6d,0xbe483f7b,0x3ec43f6d,0xbe483f7b,0xbf783e79,0xbf71beac,0x3e793f78,0xbeac3f71,
  0xbdc9bf7f,0x3ef1bf62,0x3dc93f7f,0xbef13f62,0x3f803d49,0x3f4e3f18,0xbd493f80,0xbf183f4e,0x3f80,0x3f6d3ec4,0x3f80,0x3f6d3ec4,
  0x3e953f75,0x3f7f3dc9,0x3f75be95,0x3dc9bf7f,0x3f0e3f55,0x3f7bbe48,0xbf0ebf55,0xbf7b3e48,0x3f463f22,0x3f62bef1,0xbf223f46,0x3ef13f62,
  0x3f808000,0x3ec4bf6d,0x3f808000,0x3ec4bf6d,0x3f75be95,0x3dc9bf7f,0xbe95bf75,0xbf7fbdc9,0x3f55bf0e,0xbe48bf7b,0xbf553f0e,0x3e483f7b,
  0x3f22bf46,0xbef1bf62,0x3f463f22,0x3f62bef1,0x3f80,0x3ec4bf6d,0x3f80,0x3ec4bf6d,0x3f223f46,0xbe95bf75,0x3f46bf22,0xbf753e95,
  0x3f7b3e48,0xbf55bf0e,0xbf7bbe48,0x3f553f0e,0x3f62bef1,0xbf7f3dc9,0x3ef13f62,0xbdc9bf7f,0x3f808000,0xbf6dbec4,0x3f808000,0xbf6dbec4,
  0x3f46bf22,0xbf753e95,0xbf22bf46,0x3e953f75,0x3e48bf7b,0xbf0e3f55,0xbe483f7b,0x3f0ebf55,0xbef1bf62,0x3dc93f7f,0x3f62bef1,0xbf7f3dc9,
  0x3f80,0xbf6dbec4,0x3f80,0xbf6dbec4,0x3f623ef1,0xbf463f22,0x3ef1bf62,0x3f223f46,0x3f55bf0e,0x3e483f7b,0xbf553f0e,0xbe48bf7b,
  0xbdc9bf7f,0x3f753e95,0x3f7fbdc9,0xbe953f75,0x3f808000,0xbec43f6d,0x3f808000,0xbec43f6d,0x3ef1bf62,0x3f223f46,0xbf62bef1,0x3f46bf22,
  0xbf0ebf55,0x3f7bbe48,0x3f0e3f55,0xbf7b3e48,0xbf7f3dc9,0x3e95bf75,0xbdc9bf7f,0x3f753e95,0x3f80,0xbec43f6d,0x3f80,0xbec43f6d,
  0x3f7f3dc9,0x3f623ef1,0x3dc9bf7f,0x3ef1bf62,0x3e48bf7b,0x3f0ebf55,0xbe483f7b,0xbf0e3f55,0xbf75be95,0xbf46bf22,0x3e95bf75,0x3f22bf46,
  0x3f808000,0x3f6d3ec4,0x3f808000,0x3f6d3ec4,0x3dc9bf7f,0x3ef1bf62,0xbf7fbdc9,0xbf62bef1,0xbf7bbe48,0xbf55bf0e,0x3f7b3e48,0x3f553f0e,
  0xbe953f75,0xbf223f46,0xbf75be95,0xbf46bf22,0x3f80,0x3f6d3ec4,0x3f80,0x3f6d3ec4,0xbe95bf75,0xbf7fbdc9,0xbf753e95,0xbdc93f7f,
  0x3f0e3f55,0x3f7bbe48,0xbf0ebf55,0xbf7b3e48,0xbf46bf22,0xbf623ef1,0x3f22bf46,0xbef1bf62,0x3f808000,0x3ec4bf6d,0x3f808000,0x3ec4bf6d,
  0xbf753e95,0xbdc93f7f,0x3e953f75,0x3f7f3dc9,0x3f55bf0e,0xbe48bf7b,0xbf553f0e,0x3e483f7b,0xbf223f46,0x3ef13f62,0xbf46bf22,0xbf623ef1,
  0x3f80,0x3ec4bf6d,0x3f80,0x3ec4bf6d,0xbf22bf46,0x3e953f75,0xbf463f22,0x3f75be95,0x3f7b3e48,0xbf55bf0e,0xbf7bbe48,0x3f553f0e,
  0xbf623ef1,0x3f7fbdc9,0xbef1bf62,0x3dc93f7f,0x3f808000,0xbf6dbec4,0x3f808000,0xbf6dbec4,0xbf463f22,0x3f75be95,0x3f223f46,0xbe95bf75,
  0x3e48bf7b,0xbf0e3f55,0xbe483f7b,0x3f0ebf55,0x3ef13f62,0xbdc9bf7f,0xbf623ef1,0x3f7fbdc9,0x3f80,0xbf6dbec4,0x3f80,0xbf6dbec4,
  0xbf62bef1,0x3f46bf22,0xbef13f62,0xbf22bf46,0x3f55bf0e,0x3e483f7b,0xbf553f0e,0xbe48bf7b,0x3dc93f7f,0xbf75be95,0xbf7f3dc9,0x3e95bf75,
  0x3f808000,0xbec43f6d,0x3f808000,0xbec43f6d,0xbef13f62,0xbf22bf46,0x3f623ef1,0xbf463f22,0xbf0ebf55,0x3f7bbe48,0x3f0e3f55,0xbf7b3e48,
  0x3f7fbdc9,0xbe953f75,0x3dc93f7f,0xbf75be95,0x3f80,0xbec43f6d,0x3f80,0xbec43f6d,0xbf7fbdc9,0xbf62bef1,0xbdc93f7f,0xbef13f62,
  0x3e48bf7b,0x3f0ebf55,0xbe483f7b,0xbf0e3f55,0x3f753e95,0x3f463f22,0xbe953f75,0xbf223f46,0x3f808000,0x3f6d3ec4,0x3f808000,0x3f6d3ec4,
  0xbdc93f7f,0xbef13f62,0x3f7f3dc9,0x3f623ef1,0xbf7bbe48,0xbf55bf0e,0x3f7b3e48,0x3f553f0e,0x3e95bf75,0x3f22bf46,0x3f753e95,0x3f463f22,
  0x3f35bf35,0xbec4bf6d,0x3f35bf35,0xbec4bf6d,0x3ef1bf62,0xbf22bf46,0xbf62bef1,0xbf463f22,0x3e48bf7b,0xbf55bf0e,0xbe483f7b,0x3f553f0e,
  0xbdc9bf7f,0xbf75be95,0x3f7fbdc9,0x3e95bf75,0xbf35bf35,0xbf6d3ec4,0xbf35bf35,0xbf6d3ec4,0xbf62bef1,0xbf463f22,0xbef13f62,0x3f223f46,
  0xbf7bbe48,0xbf0e3f55,0x3f7b3e48,0x3f0ebf55,0xbf7f3dc9,0xbe953f75,0xbdc9bf7f,0xbf75be95,0xbf353f35,0x3f6dbec4,0xbf353f35,0x3f6dbec4,
  0xbdc93f7f,0x3ef1bf62,0x3f7f3dc9,0xbf62bef1,0x3f0e3f55,0xbe48bf7b,0xbf0ebf55,0x3e483f7b,0x3f753e95,0xbf46bf22,0xbe953f75,0x3f22bf46,
  0x3f353f35,0xbec4bf6d,0x3f353f35,0xbec4bf6d,0x3f7f3dc9,0xbf62bef1,0x3dc9bf7f,0xbef13f62,0x3f55bf0e,0xbf7b3e48,0xbf553f0e,0x3f7bbe48,
  0x3e95bf75,0xbf223f46,0x3f753e95,0xbf46bf22,0x3f35bf35,0x3ec43f6d,0x3f35bf35,0x3ec43f6d,0xbe95bf75,0x3f7f3dc9,0xbf753e95,0x3dc9bf7f,
  0xbf7bbe48,0x3f0ebf55,0x3f7b3e48,0xbf0e3f55,0xbf223f46,0xbef1bf62,0xbf46bf22,0x3f62bef1,0xbf35bf35,0x3f6dbec4,0xbf35bf35,0x3f6dbec4,
  0xbf753e95,0x3dc9bf7f,0x3e953f75,0xbf7fbdc9,0xbe483f7b,0xbf55bf0e,0x3e48bf7b,0x3f553f0e,0x3f463f22,0xbf623ef1,0xbf223f46,0xbef1bf62,
  0xbf353f35,0xbf6d3ec4,0xbf353f35,0xbf6d3ec4,0x3f223f46,0x3e953f75,0x3f46bf22,0x3f75be95,0x3f55bf0e,0x3f7bbe48,0xbf553f0e,0xbf7b3e48,
  0xbef1bf62,0xbdc9bf7f,0x3f62bef1,0x3f7fbdc9,0x3f353f35,0x3ec43f6d,0x3f353f35,0x3ec43f6d,0x3f46bf22,0x3f75be95,0xbf22bf46,0xbe95bf75,
  0xbf0ebf55,0xbe48bf7b,0x3f0e3f55,0x3e483f7b,0xbf623ef1,0xbf7f3dc9,0xbef1bf62,0xbdc9bf7f,0x3f35bf35,0xbec4bf6d,0x3f35bf35,0xbec4bf6d,
  0xbef13f62,0x3f223f46,0x3f623ef1,0x3f46bf22,0x3e48bf7b,0xbf55bf0e,0xbe483f7b,0x3f553f0e,0x3dc93f7f,0x3f753e95,0xbf7f3dc9,0xbe953f75,
  0xbf35bf35,0xbf6d3ec4,0xbf35bf35,0xbf6d3ec4,0x3f623ef1,0x3f46bf22,0x3ef1bf62,0xbf22bf46,0xbf7bbe48,0xbf0e3f55,0x3f7b3e48,0x3f0ebf55,
  0x3f7fbdc9,0x3e95bf75,0x3dc93f7f,0x3f753e95,0xbf353f35,0x3f6dbec4,0xbf353f35,0x3f6dbec4,0x3dc9bf7f,0xbef13f62,0xbf7fbdc9,0x3f623ef1,
  0x3f0e3f55,0xbe48bf7b,0xbf0ebf55,0x3e483f7b,0xbf75be95,0x3f463f22,0x3e95bf75,0xbf223f46,0x3f353f35,0xbec4bf6d,0x3f353f35,0xbec4bf6d,
  0xbf7fbdc9,0x3f623ef1,0xbdc93f7f,0x3ef1bf62,0x3f55bf0e,0xbf7b3e48,0xbf553f0e,0x3f7bbe48,0xbe953f75,0x3f22bf46,0xbf75be95,0x3f463f22,
  0x3f35bf35,0x3ec43f6d,0x3f35bf35,0x3ec43f6d,0x3e953f75,0xbf7fbdc9,0x3f75be95,0xbdc93f7f,0xbf7bbe48,0x3f0ebf55,0x3f7b3e48,0xbf0e3f55,
  0x3f22bf46,0x3ef13f62,0x3f463f22,0xbf623ef1,0xbf35bf35,0x3f6dbec4,0xbf35bf35,0x3f6dbec4,0x3f75be95,0xbdc93f7f,0xbe95bf75,0x3f7f3dc9,
  0xbe483f7b,0xbf55bf0e,0x3e48bf7b,0x3f553f0e,0xbf46bf22,0x3f62bef1,0x3f22bf46,0x3ef13f62,0xbf353f35,0xbf6d3ec4,0xbf353f35,0xbf6d3ec4,
  0xbf22bf46,0xbe95bf75,0xbf463f22,0xbf753e95,0x3f55bf0e,0x3f7bbe48,0xbf553f0e,0xbf7b3e48,0x3ef13f62,0x3dc93f7f,0xbf623ef1,0xbf7f3dc9,
  0x3f353f35,0x3ec43f6d,0x3f353f35,0x3ec43f6d,0xbf463f22,0xbf753e95,0x3f223f46,0x3e953f75,0xbf0ebf55,0xbe48bf7b,0x3f0e3f55,0x3e483f7b,
  0x3f62bef1,0x3f7fbdc9,0x3ef13f62,0x3dc93f7f,0x3f80,0x3f7b3e48,0x3f80,0x3f7b3e48,0x3eac3f71,0x3f7dbe16,0x3f71beac,0xbe16bf7d,
  0x3f223f46,0x3f62bef1,0xbf22bf46,0xbf623ef1,0x3f5c3f04,0x3f2cbf3e,0xbf043f5c,0x3f3e3f2c,0x3f808000,0x3e48bf7b,0x3f808000,0x3e48bf7b,
  0x3f71beac,0xbe16bf7d,0xbeacbf71,0xbf7d3e16,0x3f46bf22,0xbef1bf62,0xbf463f22,0x3ef13f62,0x3f04bf5c,0xbf3ebf2c,0x3f5c3f04,0x3f2cbf3e,
  0x3f80,0x3e48bf7b,0x3f80,0x3e48bf7b,0x3f2c3f3e,0xbf04bf5c,0x3f3ebf2c,0xbf5c3f04,0x3f7f3dc9,0xbf75be95,0xbf7fbdc9,0x3f753e95,
  0x3f4ebf18,0xbf673edb,0x3f183f4e,0xbedbbf67,0x3f808000,0xbf7bbe48,0x3f808000,0xbf7bbe48,0x3f3ebf2c,0xbf5c3f04,0xbf2cbf3e,0x3f043f5c,
  0x3dc9bf7f,0xbe953f75,0xbdc93f7f,0x3e95bf75,0xbf18bf4e,0x3edb3f67,0x3f4ebf18,0xbf673edb,0x3f80,0xbf7bbe48,0x3f80,0xbf7bbe48,
  0x3f673edb,0xbf183f4e,0x3edbbf67,0x3f4e3f18,0x3f46bf22,0x3ef13f62,0xbf463f22,0xbef1bf62,0xbe79bf78,0x3f80bd49,0x3f78be79,0x3d493f80,
  0x3f808000,0xbe483f7b,0x3f808000,0xbe483f7b,0x3edbbf67,0x3f4e3f18,0xbf67bedb,0x3f18bf4e,0xbf22bf46,0x3f62bef1,0x3f223f46,0xbf623ef1,
  0xbf783e79,0xbd49bf80,0xbe79bf78,0x3f80bd49,0x3f80,0xbe483f7b,0x3f80,0xbe483f7b,0x3f803d49,0x3f783e79,0x3d49bf80,0x3e79bf78,
  0x3dc9bf7f,0x3e95bf75,0xbdc93f7f,0xbe953f75,0xbf7dbe16,0xbf71beac,0x3e16bf7d,0x3eacbf71,0x3f808000,0x3f7b3e48,0x3f808000,0x3f7b3e48,
  0x3d49bf80,0x3e79bf78,0xbf80bd49,0xbf78be79,0xbf7fbdc9,0xbf75be95,0x3f7f3dc9,0x3f753e95,0xbe163f7d,0xbeac3f71,0xbf7dbe16,0xbf71beac,
  0x3f80,0x3f7b3e48,0x3f80,0x3f7b3e48,0xbeacbf71,0xbf7d3e16,0xbf713eac,0x3e163f7d,0x3f223f46,0x3f62bef1,0xbf22bf46,0xbf623ef1,
  0xbf5cbf04,0xbf2c3f3e,0x3f04bf5c,0xbf3ebf2c,0x3f808000,0x3e48bf7b,0x3f808000,0x3e48bf7b,0xbf713eac,0x3e163f7d,0x3eac3f71,0x3f7dbe16,
  0x3f46bf22,0xbef1bf62,0xbf463f22,0x3ef13f62,0xbf043f5c,0x3f3e3f2c,0xbf5cbf04,0xbf2c3f3e,0x3f80,0x3e48bf7b,0x3f80,0x3e48bf7b,
  0xbf2cbf3e,0x3f043f5c,0xbf3e3f2c,0x3f5cbf04,0x3f7f3dc9,0xbf75be95,0xbf7fbdc9,0x3f753e95,0xbf4e3f18,0x3f67bedb,0xbf18bf4e,0x3edb3f67,
  0x3f808000,0xbf7bbe48,0x3f808000,0xbf7bbe48,0xbf3e3f2c,0x3f5cbf04,0x3f2c3f3e,0xbf04bf5c,0x3dc9bf7f,0xbe953f75,0xbdc93f7f,0x3e95bf75,
  0x3f183f4e,0xbedbbf67,0xbf4e3f18,0x3f67bedb,0x3f80,0xbf7bbe48,0x3f80,0xbf7bbe48,0xbf67bedb,0x3f18bf4e,0xbedb3f67,0xbf4ebf18,
  0x3f46bf22,0x3ef13f62,0xbf463f22,0xbef1bf62,0x3e793f78,0xbf803d49,0xbf783e79,0xbd49bf80,0x3f808000,0xbe483f7b,0x3f808000,0xbe483f7b,
  0xbedb3f67,0xbf4ebf18,0x3f673edb,0xbf183f4e,0xbf22bf46,0x3f62bef1,0x3f223f46,0xbf623ef1,0x3f78be79,0x3d493f80,0x3e793f78,0xbf803d49,
  0x3f80,0xbe483f7b,0x3f80,0xbe483f7b,0xbf80bd49,0xbf78be79,0xbd493f80,0xbe793f78,0x3dc9bf7f,0x3e95bf75,0xbdc93f7f,0xbe953f75,
  0x3f7d3e16,0x3f713eac,0xbe163f7d,0xbeac3f71,0x3f808000,0x3f7b3e48,0x3f808000,0x3f7b3e48,0xbd493f80,0xbe793f78,0x3f803d49,0x3f783e79,
  0xbf7fbdc9,0xbf75be95,0x3f7f3dc9,0x3f753e95,0x3e16bf7d,0x3eacbf71,0x3f7d3e16,0x3f713eac,0x3ec4bf6d,0xbf55bf0e,0x3ec4bf6d,0xbf55bf0e,
  0x3d49bf80,0xbf78be79,0xbf80bd49,0xbe793f78,0xbe95bf75,0xbf7f3dc9,0x3e953f75,0x3f7fbdc9,0xbf18bf4e,0xbf673edb,0x3f4ebf18,0xbedbbf67,
  0xbf6dbec4,0xbf0e3f55,0xbf6dbec4,0xbf0e3f55,0xbf80bd49,0xbe793f78,0xbd493f80,0x3f783e79,0xbf753e95,0x3dc93f7f,0x3f75be95,0xbdc9bf7f,
  0xbf4e3f18,0x3edb3f67,0xbf18bf4e,0xbf673edb,0xbec43f6d,0x3f0ebf55,0xbec43f6d,0x3f0ebf55,0x3eac3f71,0xbe16bf7d,0x3f71beac,0xbf7d3e16,
  0x3f623ef1,0xbf46bf22,0xbf62bef1,0x3f463f22,0x3f78be79,0xbf803d49,0x3e793f78,0xbd49bf80,0x3f6d3ec4,0xbf55bf0e,0x3f6d3ec4,0xbf55bf0e,
  0x3f71beac,0xbf7d3e16,0xbeacbf71,0x3e163f7d,0x3ef1bf62,0xbf223f46,0xbef13f62,0x3f22bf46,0xbe79bf78,0x3d493f80,0x3f78be79,0xbf803d49,
  0x3ec4bf6d,0x3f553f0e,0x3ec4bf6d,0x3f553f0e,0xbf2cbf3e,0x3f5cbf04,0xbf3e3f2c,0xbf04bf5c,0xbf753e95,0xbdc9bf7f,0x3f75be95,0x3dc93f7f,
  0xbe163f7d,0xbf71beac,0xbf7dbe16,0x3eacbf71,0xbf6dbec4,0x3f0ebf55,0xbf6dbec4,0x3f0ebf55,0xbf3e3f2c,0xbf04bf5c,0x3f2c3f3e,0xbf5c3f04,
  0x3e953f75,0xbf7f3dc9,0xbe95bf75,0x3f7fbdc9,0x3f7d3e16,0xbeac3f71,0xbe163f7d,0xbf71beac,0xbec43f6d,0xbf0e3f55,0xbec43f6d,0xbf0e3f55,
  0x3f673edb,0x3f4e3f18,0x3edbbf67,0x3f18bf4e,0x3ef1bf62,0x3f22bf46,0xbef13f62,0xbf223f46,0xbf5cbf04,0xbf3ebf2c,0x3f04bf5c,0x3f2cbf3e,
  0x3f6d3ec4,0x3f553f0e,0x3f6d3ec4,0x3f553f0e,0x3edbbf67,0x3f18bf4e,0xbf67bedb,0xbf4ebf18,0xbf62bef1,0xbf46bf22,0x3f623ef1,0x3f463f22,
  0xbf043f5c,0xbf2c3f3e,0xbf5cbf04,0xbf3ebf2c,0x3ec4bf6d,0xbf55bf0e,0x3ec4bf6d,0xbf55bf0e,0xbd493f80,0x3f783e79,0x3f803d49,0x3e79bf78,
  0xbe95bf75,0xbf7f3dc9,0x3e953f75,0x3f7fbdc9,0x3f183f4e,0x3f67bedb,0xbf4e3f18,0x3edb3f67,0xbf6dbec4,0xbf0e3f55,0xbf6dbec4,0xbf0e3f55,
  0x3f803d49,0x3e79bf78,0x3d49bf80,0xbf78be79,0xbf753e95,0x3dc93f7f,0x3f75be95,0xbdc9bf7f,0x3f4ebf18,0xbedbbf67,0x3f183f4e,0x3f67bedb,
  0xbec43f6d,0x3f0ebf55,0xbec43f6d,0x3f0ebf55,0xbeacbf71,0x3e163f7d,0xbf713eac,0x3f7dbe16,0x3f623ef1,0xbf46bf22,0xbf62bef1,0x3f463f22,
  0xbf783e79,0x3f80bd49,0xbe79bf78,0x3d493f80,0x3f6d3ec4,0xbf55bf0e,0x3f6d3ec4,0xbf55bf0e,0xbf713eac,0x3f7dbe16,0x3eac3f71,0xbe16bf7d,
  0x3ef1bf62,0xbf223f46,0xbef13f62,0x3f22bf46,0x3e793f78,0xbd49bf80,0xbf783e79,0x3f80bd49,0x3ec4bf6d,0x3f553f0e,0x3ec4bf6d,0x3f553f0e,
  0x3f2c3f3e,0xbf5c3f04,0x3f3ebf2c,0x3f043f5c,0xbf753e95,0xbdc9bf7f,0x3f75be95,0x3dc93f7f,0x3e16bf7d,0x3f713eac,0x3f7d3e16,0xbeac3f71,
  0xbf6dbec4,0x3f0ebf55,0xbf6dbec4,0x3f0ebf55,0x3f3ebf2c,0x3f043f5c,0xbf2cbf3e,0x3f5cbf04,0x3e953f75,0xbf7f3dc9,0xbe95bf75,0x3f7fbdc9,
  0xbf7dbe16,0x3eacbf71,0x3e16bf7d,0x3f713eac,0xbec43f6d,0xbf0e3f55,0xbec43f6d,0xbf0e3f55,0xbf67bedb,0xbf4ebf18,0xbedb3f67,0xbf183f4e,
  0x3ef1bf62,0x3f22bf46,0xbef13f62,0xbf223f46,0x3f5c3f04,0x3f3e3f2c,0xbf043f5c,0xbf2c3f3e,0x3f6d3ec4,0x3f553f0e,0x3f6d3ec4,0x3f553f0e,
  0xbedb3f67,0xbf183f4e,0x3f673edb,0x3f4e3f18,0xbf62bef1,0xbf46bf22,0x3f623ef1,0x3f463f22,0x3f04bf5c,0x3f2cbf3e,0x3f5c3f04,0x3f3e3f2c,
};

constexpr int TP = 16512;
constexpr int SLOT = 32768;
constexpr int NSLOT = 7;
constexpr int XSLOT = 3;
constexpr int SCR = 5 * SLOT;
constexpr int EXA = SCR;
constexpr int EXB = SCR + 19456;
constexpr int WST = SCR + 35840;
constexpr int TABO = 3 * SLOT;
constexpr int T_FR = SCR + 60416, T_FI = T_FR + 512, T_TW = T_FR + 1024, T_BF = T_FR + 3072, T_AR = EXB, T_AI = EXB + 512;
constexpr int T_G = TABO;
constexpr int AST = 3 * SLOT;
constexpr int BAR = 7 * SLOT;
constexpr int B_FULL = BAR, B_EMPTY = BAR + 56, B_W = BAR + 112, B_XFREE = BAR + 120, B_X = BAR + 128, B_T = BAR + 192, DUMMY = BAR + 208, EPO = BAR + 212, TOK = BAR + 224, B_A = BAR + 256, B_AE = BAR + 512;
constexpr int SMEM_BYTES = BAR + 768;

constexpr int SY_FL = 0, SY_HR = 1088, SY_H = 2112, SY_WORDS = 4160;

struct Params {
  const uint32_t* x;
  uint32_t* out;
  char* T;
  char* HR;
  char* H;
  char* WX;
  uint32_t* sync;
  const uint4* tab;
  const char *wg, *wu, *wd;
  const unsigned short *wr, *wi;
  long long* dbg;
};

__device__ uint4 g_T[128 * TP / 16];
__device__ uint4 g_HR[128 * 1024];
__device__ uint4 g_H[128 * 3 * 1024];
__device__ uint4 g_WX[1024];
__device__ uint32_t g_sync[SY_WORDS];
#define TS(i)
#define TS_FLUSH()

constexpr int SPIN_LIMIT = 1 << 18;

__device__ __forceinline__ uint32_t pack_bf16(float lo, float hi) {
  uint32_t r; asm("cvt.rn.bf16x2.f32 %0, %1, %2;" : "=r"(r) : "f"(hi), "f"(lo)); return r;
}
__device__ __forceinline__ float bf_lo(uint32_t w) { return __uint_as_float(w << 16); }
__device__ __forceinline__ float bf_hi(uint32_t w) { return __uint_as_float(w & 0xffff0000u); }
__device__ __forceinline__ float round_bf16(float v) { return bf_lo(pack_bf16(v, 0.f)); }
__device__ __forceinline__ uint32_t prmt(uint32_t a, uint32_t b, uint32_t s) {
  uint32_t r; asm("prmt.b32 %0, %1, %2, %3;" : "=r"(r) : "r"(a), "r"(b), "r"(s)); return r;
}
__device__ __forceinline__ uint32_t hadd2b(uint32_t a, uint32_t b) { uint32_t r; asm("add.rn.bf16x2 %0, %1, %2;" : "=r"(r) : "r"(a), "r"(b)); return r; }
__device__ __forceinline__ uint32_t hsub2b(uint32_t a, uint32_t b) { uint32_t r; asm("sub.rn.bf16x2 %0, %1, %2;" : "=r"(r) : "r"(a), "r"(b)); return r; }
__device__ __forceinline__ uint32_t hmul2b(uint32_t a, uint32_t b) { uint32_t r; asm("mul.rn.bf16x2 %0, %1, %2;" : "=r"(r) : "r"(a), "r"(b)); return r; }
__device__ __forceinline__ uint32_t hfma2b(uint32_t a, uint32_t b, uint32_t c) { uint32_t r; asm("fma.rn.bf16x2 %0, %1, %2, %3;" : "=r"(r) : "r"(a), "r"(b), "r"(c)); return r; }
__device__ __forceinline__ uint32_t tag0(uint32_t w) { return w & 0xfffffffeu; }
__device__ __forceinline__ uint32_t tag1(uint32_t w) { return w | 1u; }
__device__ __forceinline__ void mma16(float (&d)[4], uint32_t a0, uint32_t a1, uint32_t a2, uint32_t a3, uint32_t b0, uint32_t b1) {
  asm("mma.sync.aligned.m16n8k16.row.col.f32.bf16.bf16.f32 {%0,%1,%2,%3}, {%4,%5,%6,%7}, {%8,%9}, {%0,%1,%2,%3};"
      : "+f"(d[0]), "+f"(d[1]), "+f"(d[2]), "+f"(d[3]) : "r"(a0), "r"(a1), "r"(a2), "r"(a3), "r"(b0), "r"(b1));
}
__device__ __forceinline__ void mma16z(float (&d)[4], uint32_t a0, uint32_t a1, uint32_t a2, uint32_t a3, uint32_t b0, uint32_t b1) {
  asm("mma.sync.aligned.m16n8k16.row.col.f32.bf16.bf16.f32 {%0,%1,%2,%3}, {%4,%5,%6,%7}, {%8,%9}, {%10,%10,%10,%10};"
      : "=f"(d[0]), "=f"(d[1]), "=f"(d[2]), "=f"(d[3]) : "r"(a0), "r"(a1), "r"(a2), "r"(a3), "r"(b0), "r"(b1), "f"(0.f));
}
__device__ __forceinline__ uint4 ldg_nc4(const void* p) {
  uint4 v; asm volatile("ld.global.nc.v4.u32 {%0,%1,%2,%3}, [%4];" : "=r"(v.x), "=r"(v.y), "=r"(v.z), "=r"(v.w) : "l"(p)); return v;
}
__device__ __forceinline__ uint2 ldg_nc2(const void* p) {
  uint2 v; asm volatile("ld.global.nc.L1::no_allocate.v2.u32 {%0,%1}, [%2];" : "=r"(v.x), "=r"(v.y) : "l"(p)); return v;
}
__device__ __forceinline__ uint32_t ldg_nc1(const void* p) {
  uint32_t v; asm volatile("ld.global.nc.L1::no_allocate.u32 %0, [%1];" : "=r"(v) : "l"(p)); return v;
}
__device__ __forceinline__ uint32_t ld_rlx(const void* p) {
  uint32_t v; asm volatile("ld.relaxed.gpu.global.u32 %0, [%1];" : "=r"(v) : "l"(p) : "memory"); return v;
}
__device__ __forceinline__ uint32_t ld_acq(const void* p) {
  uint32_t v; asm volatile("ld.acquire.gpu.global.u32 %0, [%1];" : "=r"(v) : "l"(p) : "memory"); return v;
}
__device__ __forceinline__ uint2 ld_rlx2(const void* p) {
  uint2 v; asm volatile("{ .reg .b64 t; ld.relaxed.gpu.global.b64 t, [%2]; mov.b64 {%0,%1}, t; }" : "=r"(v.x), "=r"(v.y) : "l"(p) : "memory"); return v;
}
__device__ __forceinline__ void ld_rlx4(const void* p, uint32_t& a, uint32_t& b, uint32_t& c, uint32_t& d) {
  asm volatile("{ .reg .b64 t, u; ld.relaxed.gpu.global.v2.b64 {t, u}, [%4]; mov.b64 {%0,%1}, t; mov.b64 {%2,%3}, u; }"
               : "=r"(a), "=r"(b), "=r"(c), "=r"(d) : "l"(p) : "memory");
}
__device__ __forceinline__ void st_rlx(void* p, uint32_t v) { asm volatile("st.relaxed.gpu.global.u32 [%0], %1;" :: "l"(p), "r"(v) : "memory"); }
__device__ __forceinline__ void st_rlx2(void* p, uint32_t a, uint32_t b) {
  asm volatile("{ .reg .b64 t; mov.b64 t, {%1,%2}; st.relaxed.gpu.global.b64 [%0], t; }" :: "l"(p), "r"(a), "r"(b) : "memory");
}
__device__ __forceinline__ void st_rlx4(void* p, uint32_t a, uint32_t b, uint32_t c, uint32_t d) {
  asm volatile("{ .reg .b64 t, u; mov.b64 t, {%1,%2}; mov.b64 u, {%3,%4}; st.relaxed.gpu.global.v2.b64 [%0], {t, u}; }"
               :: "l"(p), "r"(a), "r"(b), "r"(c), "r"(d) : "memory");
}
__device__ __forceinline__ void st_rlx_u8(void* p, uint32_t v) { asm volatile("st.relaxed.gpu.global.u8 [%0], %1;" :: "l"(p), "r"(v) : "memory"); }
__device__ __forceinline__ void stg4(void* p, uint32_t a, uint32_t b, uint32_t c, uint32_t d) {
  asm volatile("st.global.v4.u32 [%0], {%1,%2,%3,%4};" :: "l"(p), "r"(a), "r"(b), "r"(c), "r"(d) : "memory");
}
__device__ __forceinline__ void stg1(void* p, uint32_t a) { asm volatile("st.global.u32 [%0], %1;" :: "l"(p), "r"(a) : "memory"); }
__device__ __forceinline__ void fence_gpu() { asm volatile("fence.acq_rel.gpu;" ::: "memory"); }
__device__ __forceinline__ void red_add(void* p, uint32_t v) { asm volatile("red.relaxed.gpu.global.add.u32 [%0], %1;" :: "l"(p), "r"(v) : "memory"); }
__device__ __forceinline__ void wait_ge_acq(const uint32_t* p, uint32_t target) {
  int it = 0;
  while ((int)(ld_acq(p) - target) < 0) { if (++it > SPIN_LIMIT) break; }
}

__device__ __forceinline__ void sts1(uint32_t a, uint32_t v) { asm volatile("st.shared.u32 [%0], %1;" :: "r"(a), "r"(v) : "memory"); }
__device__ __forceinline__ void sts2(uint32_t a, uint32_t v, uint32_t w) { asm volatile("st.shared.v2.u32 [%0], {%1,%2};" :: "r"(a), "r"(v), "r"(w) : "memory"); }
__device__ __forceinline__ uint32_t lds1(uint32_t a) { uint32_t v; asm volatile("ld.shared.u32 %0, [%1];" : "=r"(v) : "r"(a) : "memory"); return v; }
__device__ __forceinline__ float lds_bf(uint32_t a) { uint16_t v; asm volatile("ld.shared.u16 %0, [%1];" : "=h"(v) : "r"(a) : "memory"); return __uint_as_float((uint32_t)v << 16); }
__device__ __forceinline__ uint2 lds2(uint32_t a) { uint2 v; asm volatile("ld.shared.v2.u32 {%0,%1}, [%2];" : "=r"(v.x), "=r"(v.y) : "r"(a) : "memory"); return v; }
__device__ __forceinline__ uint4 lds4(uint32_t a) { uint4 v; asm volatile("ld.shared.v4.u32 {%0,%1,%2,%3}, [%4];" : "=r"(v.x), "=r"(v.y), "=r"(v.z), "=r"(v.w) : "r"(a) : "memory"); return v; }
__device__ __forceinline__ uint4 ldsm4(uint32_t a) { uint4 v; asm volatile("ldmatrix.sync.aligned.m8n8.x4.shared.b16 {%0,%1,%2,%3}, [%4];" : "=r"(v.x), "=r"(v.y), "=r"(v.z), "=r"(v.w) : "r"(a) : "memory"); return v; }
__device__ __forceinline__ uint4 ldsm4t(uint32_t a) { uint4 v; asm volatile("ldmatrix.sync.aligned.m8n8.x4.trans.shared.b16 {%0,%1,%2,%3}, [%4];" : "=r"(v.x), "=r"(v.y), "=r"(v.z), "=r"(v.w) : "r"(a) : "memory"); return v; }
__device__ __forceinline__ uint2 ldsm2t(uint32_t a) { uint2 v; asm volatile("ldmatrix.sync.aligned.m8n8.x2.trans.shared.b16 {%0,%1}, [%2];" : "=r"(v.x), "=r"(v.y) : "r"(a) : "memory"); return v; }
__device__ __forceinline__ void stsm4(uint32_t a, uint32_t r0, uint32_t r1, uint32_t r2, uint32_t r3) {
  asm volatile("stmatrix.sync.aligned.m8n8.x4.shared.b16 [%0], {%1,%2,%3,%4};" :: "r"(a), "r"(r0), "r"(r1), "r"(r2), "r"(r3) : "memory");
}
__device__ __forceinline__ void pin(uint32_t dummy, uint32_t v) { asm volatile("{ .reg .pred p; setp.eq.u32 p, %1, 0x7fedcba9; @p st.shared.u32 [%0], %1; }" :: "r"(dummy), "r"(v) : "memory"); }
__device__ __forceinline__ void bar_sync(int id, int n) { asm volatile("bar.sync %0, %1;" :: "r"(id), "r"(n) : "memory"); }
__device__ __forceinline__ void bar_arrive(int id, int n) { asm volatile("bar.arrive %0, %1;" :: "r"(id), "r"(n) : "memory"); }

__device__ __forceinline__ void mbar_init(uint32_t b, int c) { asm volatile("mbarrier.init.shared::cta.b64 [%0], %1;" :: "r"(b), "r"(c) : "memory"); }
__device__ __forceinline__ void mbar_expect(uint32_t b, int bytes) { asm volatile("mbarrier.arrive.expect_tx.shared::cta.b64 _, [%0], %1;" :: "r"(b), "r"(bytes) : "memory"); }
__device__ __forceinline__ void mbar_arrive(uint32_t b) { asm volatile("mbarrier.arrive.shared::cta.b64 _, [%0];" :: "r"(b) : "memory"); }
__device__ __forceinline__ void mbar_wait(uint32_t b, uint32_t par) {
  uint32_t ok; int it = 0;
  do {
    asm volatile("{ .reg .pred p; mbarrier.try_wait.parity.shared::cta.b64 p, [%1], %2; selp.u32 %0, 1, 0, p; }" : "=r"(ok) : "r"(b), "r"(par) : "memory");
    if (++it > SPIN_LIMIT) break;
  } while (!ok);
}
__device__ __forceinline__ void mbar_wait_cluster(uint32_t b, uint32_t par) {
  uint32_t ok; int it = 0;
  do {
    asm volatile("{ .reg .pred p; mbarrier.try_wait.parity.acquire.cluster.shared::cta.b64 p, [%1], %2; selp.u32 %0, 1, 0, p; }" : "=r"(ok) : "r"(b), "r"(par) : "memory");
    if (++it > SPIN_LIMIT) break;
  } while (!ok);
}
__device__ __forceinline__ void tma2d(uint32_t dst, const CUtensorMap* m, int c0, int c1, uint32_t bar) {
  asm volatile("cp.async.bulk.tensor.2d.shared::cluster.global.mbarrier::complete_tx::bytes [%0], [%1, {%3, %4}], [%2];"
               :: "r"(dst), "l"(m), "r"(bar), "r"(c0), "r"(c1) : "memory");
}
__device__ __forceinline__ void tma3d(uint32_t dst, const CUtensorMap* m, int c0, int c1, int c2, uint32_t bar) {
  asm volatile("cp.async.bulk.tensor.3d.shared::cluster.global.mbarrier::complete_tx::bytes [%0], [%1, {%3, %4, %5}], [%2];"
               :: "r"(dst), "l"(m), "r"(bar), "r"(c0), "r"(c1), "r"(c2) : "memory");
}
__device__ __forceinline__ void bulk_load(uint32_t dst, const void* src, int bytes, uint32_t bar) {
  asm volatile("cp.async.bulk.shared::cluster.global.mbarrier::complete_tx::bytes [%0], [%1], %2, [%3];"
               :: "r"(dst), "l"(src), "r"(bytes), "r"(bar) : "memory");
}
__device__ __forceinline__ void bulk_store(void* dst, uint32_t src, int bytes) {
  asm volatile("cp.async.bulk.global.shared::cta.bulk_group [%0], [%1], %2;" :: "l"(dst), "r"(src), "r"(bytes) : "memory");
}
__device__ __forceinline__ float ldg_bf(const unsigned short* p) { unsigned short v; asm volatile("ld.global.nc.u16 %0, [%1];" : "=h"(v) : "l"(p)); return __uint_as_float((uint32_t)v << 16); }
__device__ __forceinline__ void wait_ge_rlx(const uint32_t* p, uint32_t target) {
  int it = 0;
  while ((int)(ld_rlx(p) - target) < 0) { if (++it > SPIN_LIMIT) break; }
}
__device__ __forceinline__ void wait_ge_sleep(const uint32_t* p, uint32_t target) {
  int it = 0;
  while ((int)(ld_rlx(p) - target) < 0) { if (++it > SPIN_LIMIT) break; __nanosleep(300); }
}
__device__ __forceinline__ void l2_prefetch(const void* src, int bytes) {
  asm volatile("cp.async.bulk.prefetch.L2.global [%0], %1;" :: "l"(src), "r"(bytes) : "memory");
}
__device__ __forceinline__ void tmap_prefetch(const CUtensorMap* m) { asm volatile("prefetch.tensormap [%0];" :: "l"(m) : "memory"); }
__device__ __forceinline__ uint64_t mkdesc(uint32_t addr, uint32_t lbo, uint32_t sbo, uint32_t swz) {
  return (uint64_t)((addr & 0x3FFFF) >> 4) | ((uint64_t)(lbo >> 4) << 16) | ((uint64_t)(sbo >> 4) << 32) | ((uint64_t)swz << 62);
}
#define WG_FENCE() asm volatile("wgmma.fence.sync.aligned;" ::: "memory")
#define WG_COMMIT() asm volatile("wgmma.commit_group.sync.aligned;" ::: "memory")
#define WG_WAIT(n) asm volatile("wgmma.wait_group.sync.aligned " #n ";" ::: "memory")

__device__ __forceinline__ void wgmma_rs_n128(float (&d)[64], uint32_t a0, uint32_t a1, uint32_t a2, uint32_t a3, uint64_t descB, int scaleD) {
  asm volatile("{ .reg .pred p; setp.ne.b32 p, %69, 0;\n"
    "wgmma.mma_async.sync.aligned.m64n128k16.f32.bf16.bf16 {%0, %1, %2, %3, %4, %5, %6, %7, %8, %9, %10, %11, %12, %13, %14, %15, %16, %17, %18, %19, %20, %21, %22, %23, %24, %25, %26, %27, %28, %29, %30, %31, %32, %33, %34, %35, %36, %37, %38, %39, %40, %41, %42, %43, %44, %45, %46, %47, %48, %49, %50, %51, %52, %53, %54, %55, %56, %57, %58, %59, %60, %61, %62, %63}, {%64,%65,%66,%67}, %68, p, 1, 1, 1; }\n"
    :
      "+f"(d[0]), "+f"(d[1]), "+f"(d[2]), "+f"(d[3]), "+f"(d[4]), "+f"(d[5]), "+f"(d[6]), "+f"(d[7]),
      "+f"(d[8]), "+f"(d[9]), "+f"(d[10]), "+f"(d[11]), "+f"(d[12]), "+f"(d[13]), "+f"(d[14]), "+f"(d[15]),
      "+f"(d[16]), "+f"(d[17]), "+f"(d[18]), "+f"(d[19]), "+f"(d[20]), "+f"(d[21]), "+f"(d[22]), "+f"(d[23]),
      "+f"(d[24]), "+f"(d[25]), "+f"(d[26]), "+f"(d[27]), "+f"(d[28]), "+f"(d[29]), "+f"(d[30]), "+f"(d[31]),
      "+f"(d[32]), "+f"(d[33]), "+f"(d[34]), "+f"(d[35]), "+f"(d[36]), "+f"(d[37]), "+f"(d[38]), "+f"(d[39]),
      "+f"(d[40]), "+f"(d[41]), "+f"(d[42]), "+f"(d[43]), "+f"(d[44]), "+f"(d[45]), "+f"(d[46]), "+f"(d[47]),
      "+f"(d[48]), "+f"(d[49]), "+f"(d[50]), "+f"(d[51]), "+f"(d[52]), "+f"(d[53]), "+f"(d[54]), "+f"(d[55]),
      "+f"(d[56]), "+f"(d[57]), "+f"(d[58]), "+f"(d[59]), "+f"(d[60]), "+f"(d[61]), "+f"(d[62]), "+f"(d[63])
    : "r"(a0), "r"(a1), "r"(a2), "r"(a3), "l"(descB), "r"(scaleD));
}
__device__ __forceinline__ void wgmma_rs_n48(float (&d)[24], uint32_t a0, uint32_t a1, uint32_t a2, uint32_t a3, uint64_t descB, int scaleD) {
  asm volatile("{ .reg .pred p; setp.ne.b32 p, %29, 0;\n"
    "wgmma.mma_async.sync.aligned.m64n48k16.f32.bf16.bf16 {%0, %1, %2, %3, %4, %5, %6, %7, %8, %9, %10, %11, %12, %13, %14, %15, %16, %17, %18, %19, %20, %21, %22, %23}, {%24,%25,%26,%27}, %28, p, 1, 1, 1; }\n"
    :
      "+f"(d[0]), "+f"(d[1]), "+f"(d[2]), "+f"(d[3]), "+f"(d[4]), "+f"(d[5]), "+f"(d[6]), "+f"(d[7]),
      "+f"(d[8]), "+f"(d[9]), "+f"(d[10]), "+f"(d[11]), "+f"(d[12]), "+f"(d[13]), "+f"(d[14]), "+f"(d[15]),
      "+f"(d[16]), "+f"(d[17]), "+f"(d[18]), "+f"(d[19]), "+f"(d[20]), "+f"(d[21]), "+f"(d[22]), "+f"(d[23])
    : "r"(a0), "r"(a1), "r"(a2), "r"(a3), "l"(descB), "r"(scaleD));
}
__device__ __forceinline__ void wgmma_ss_n128(float (&d)[64], uint64_t descA, uint64_t descB, int scaleD) {
  asm volatile("{ .reg .pred p; setp.ne.b32 p, %66, 0;\n"
    "wgmma.mma_async.sync.aligned.m64n128k16.f32.bf16.bf16 {%0, %1, %2, %3, %4, %5, %6, %7, %8, %9, %10, %11, %12, %13, %14, %15, %16, %17, %18, %19, %20, %21, %22, %23, %24, %25, %26, %27, %28, %29, %30, %31, %32, %33, %34, %35, %36, %37, %38, %39, %40, %41, %42, %43, %44, %45, %46, %47, %48, %49, %50, %51, %52, %53, %54, %55, %56, %57, %58, %59, %60, %61, %62, %63}, %64, %65, p, 1, 1, 0, 1; }\n"
    :
      "+f"(d[0]), "+f"(d[1]), "+f"(d[2]), "+f"(d[3]), "+f"(d[4]), "+f"(d[5]), "+f"(d[6]), "+f"(d[7]),
      "+f"(d[8]), "+f"(d[9]), "+f"(d[10]), "+f"(d[11]), "+f"(d[12]), "+f"(d[13]), "+f"(d[14]), "+f"(d[15]),
      "+f"(d[16]), "+f"(d[17]), "+f"(d[18]), "+f"(d[19]), "+f"(d[20]), "+f"(d[21]), "+f"(d[22]), "+f"(d[23]),
      "+f"(d[24]), "+f"(d[25]), "+f"(d[26]), "+f"(d[27]), "+f"(d[28]), "+f"(d[29]), "+f"(d[30]), "+f"(d[31]),
      "+f"(d[32]), "+f"(d[33]), "+f"(d[34]), "+f"(d[35]), "+f"(d[36]), "+f"(d[37]), "+f"(d[38]), "+f"(d[39]),
      "+f"(d[40]), "+f"(d[41]), "+f"(d[42]), "+f"(d[43]), "+f"(d[44]), "+f"(d[45]), "+f"(d[46]), "+f"(d[47]),
      "+f"(d[48]), "+f"(d[49]), "+f"(d[50]), "+f"(d[51]), "+f"(d[52]), "+f"(d[53]), "+f"(d[54]), "+f"(d[55]),
      "+f"(d[56]), "+f"(d[57]), "+f"(d[58]), "+f"(d[59]), "+f"(d[60]), "+f"(d[61]), "+f"(d[62]), "+f"(d[63])
    : "l"(descA), "l"(descB), "r"(scaleD));
}

struct DConst { uint4 fr, fi, nfi, tw[4]; };
__device__ __forceinline__ uint4 xor4(const uint4& v, uint32_t m) { return make_uint4(v.x ^ m, v.y ^ m, v.z ^ m, v.w ^ m); }
__device__ __forceinline__ uint4 swap4(const uint4& v) { return make_uint4(v.x, v.z, v.y, v.w); }
__device__ __forceinline__ void dstage(const DConst& k, const uint4& fr2, const uint4& nfi2, const uint4& ia, const uint4& ib,
                                       const uint32_t (&bre)[2][2], const uint32_t (&bim)[2][2], float (&ore)[2][4], float (&oim)[2][4]) {
  float cr[2][4], ci[2][4];
#pragma unroll
  for (int t = 0; t < 2; t++) {
    mma16z(cr[t], k.fr.x, k.fr.y, k.fr.z, k.fr.w, bre[t][0], bre[t][1]);
    mma16z(ci[t], k.fi.x, k.fi.y, k.fi.z, k.fi.w, bre[t][0], bre[t][1]);
  }
#pragma unroll
  for (int t = 0; t < 2; t++) {
    mma16(cr[t], nfi2.x, nfi2.y, nfi2.z, nfi2.w, bim[t][0], bim[t][1]);
    mma16(ci[t], fr2.x, fr2.y, fr2.z, fr2.w, bim[t][0], bim[t][1]);
  }
  float zr[2][4], zi[2][4];
#pragma unroll
  for (int hi = 0; hi < 2; hi++)
#pragma unroll
    for (int q = 0; q < 4; q++) {
      const uint4 tw = k.tw[2 * hi + (q >> 1)];
      const float tr = __uint_as_float((q & 1) ? tw.z : tw.x), ti = __uint_as_float((q & 1) ? tw.w : tw.y);
      const float a = cr[q & 1][2 * hi + (q >> 1)], b = ci[q & 1][2 * hi + (q >> 1)];
      zr[hi][q] = fmaf(a, tr, -b * ti);
      zi[hi][q] = fmaf(a, ti, b * tr);
    }
  const uint32_t r0 = pack_bf16(zr[0][0], zr[0][1]), r1 = pack_bf16(zr[1][0], zr[1][1]), r2 = pack_bf16(zr[0][2], zr[0][3]), r3 = pack_bf16(zr[1][2], zr[1][3]);
  const uint32_t i0 = pack_bf16(zi[0][0], zi[0][1]), i1 = pack_bf16(zi[1][0], zi[1][1]), i2 = pack_bf16(zi[0][2], zi[0][3]), i3 = pack_bf16(zi[1][2], zi[1][3]);
  mma16z(ore[0], r0, r1, r2, r3, k.fr.x, k.fr.z);
  mma16z(oim[0], r0, r1, r2, r3, ia.x, ia.y);
  mma16z(ore[1], r0, r1, r2, r3, k.fr.y, k.fr.w);
  mma16z(oim[1], r0, r1, r2, r3, ia.z, ia.w);
  mma16(ore[0], i0, i1, i2, i3, k.nfi.x, k.nfi.z);
  mma16(oim[0], i0, i1, i2, i3, ib.x, ib.y);
  mma16(ore[1], i0, i1, i2, i3, k.nfi.y, k.nfi.w);
  mma16(oim[1], i0, i1, i2, i3, ib.z, ib.w);
}
__device__ __forceinline__ void r16(float (&o)[4][4], const uint2 (&a)[4], const uint32_t (&b)[16]) {
#pragma unroll
  for (int t = 0; t < 4; t++) mma16z(o[t], a[0].x, a[0].y, a[1].x, a[1].y, b[2 * t], b[2 * t + 1]);
#pragma unroll
  for (int t = 0; t < 4; t++) mma16(o[t], a[2].x, a[2].y, a[3].x, a[3].y, b[8 + 2 * t], b[8 + 2 * t + 1]);
}
__device__ __forceinline__ float row_sum(const uint32_t (&b)[8]) {
  const uint32_t one = 0x3f803f80u;
  float s0[4], s1[4];
  mma16z(s0, one, one, one, one, b[0], b[1]);
  mma16z(s1, one, one, one, one, b[2], b[3]);
  mma16(s0, one, one, one, one, b[4], b[5]);
  mma16(s1, one, one, one, one, b[6], b[7]);
  float s = (s0[0] + s0[1]) + (s1[0] + s1[1]);
  s += __shfl_xor_sync(0xffffffffu, s, 1);
  s += __shfl_xor_sync(0xffffffffu, s, 2);
  return s;
}
__device__ __forceinline__ float ln_center(uint32_t (&b)[8]) {
  const float mean = row_sum(b) * (1.f / 512.f);
  const uint32_t mb = pack_bf16(mean, mean);
  uint32_t sq[8];
#pragma unroll
  for (int i = 0; i < 8; i++) { b[i] = hsub2b(b[i], mb); sq[i] = hmul2b(b[i], b[i]); }
  const float dm = mean - bf_lo(mb);
  const float var = fmaf(row_sum(sq), 1.f / 512.f, -dm * dm);
  float sd, r;
  asm("sqrt.approx.ftz.f32 %0, %1;" : "=f"(sd) : "f"(round_bf16(round_bf16(var) + 1e-5f)));
  asm("rcp.approx.ftz.f32 %0, %1;" : "=f"(r) : "f"(round_bf16(sd)));
  return r;
}
__device__ __forceinline__ float gelu2_mul(float g, float u) {
  const float t = g * g;
  const float a = g * fmaf(t, 0.7978845608f * 0.044715f, 0.7978845608f);
  float th; asm("tanh.approx.f32 %0, %1;" : "=f"(th) : "f"(a));
  const float gu = g * u;
  return fmaf(gu, th, gu);
}

struct Maps { CUtensorMap wg, wu, wd64, wd16, wr, wi; };

__device__ __forceinline__ void issue_g1(const Maps& mp, uint32_t sb, int s, int f0) {
  const int slot = s % NSLOT;
  const uint32_t bar = sb + B_FULL + slot * 8, dst = sb + slot * SLOT;
  mbar_expect(bar, 16384);
  tma2d(dst, &mp.wg, f0 + 64 * (s >> 2), 128 * (s & 3), bar);
  mbar_expect(bar, 16384);
  tma2d(dst + 16384, &mp.wu, f0 + 64 * (s >> 2), 128 * (s & 3), bar);
}
__device__ __forceinline__ void issue_g1_half(const Maps& mp, uint32_t sb, int s, int f0, int half) {
  const int slot = s % NSLOT;
  const uint32_t bar = sb + B_FULL + slot * 8;
  mbar_expect(bar, 16384);
  tma2d(sb + slot * SLOT + half * 16384, half ? &mp.wu : &mp.wg, f0 + 64 * (s >> 2), 128 * (s & 3), bar);
}
__device__ __forceinline__ void acquire_slot(uint32_t sb, int s) {
  const int slot = s % NSLOT, n = s / NSLOT;
  int it = 0;
  uint32_t v;
  while (true) {
    asm volatile("ld.volatile.shared.u32 %0, [%1];" : "=r"(v) : "r"(sb + TOK + slot * 4) : "memory");
    if ((int)v == n - 1 || ++it > SPIN_LIMIT) break;
    __nanosleep(200);
  }
  mbar_wait(sb + B_EMPTY + slot * 8, (n - 1) & 1);
  asm volatile("st.volatile.shared.u32 [%0], %1;" :: "r"(sb + TOK + slot * 4), "r"(n) : "memory");
}
__device__ __forceinline__ uint32_t and4(const uint2 (&a)[4]) { return a[0].x & a[1].x & a[2].x & a[3].x; }
__device__ __forceinline__ uint32_t or4(const uint2 (&a)[4]) { return a[0].x | a[1].x | a[2].x | a[3].x; }
__device__ __forceinline__ void sincos_idx(int idx, float scale, float& sn, float& cs) { __sincosf((float)idx * scale, &sn, &cs); }
__device__ __forceinline__ void sts_h(uint32_t a, float v) { asm volatile("st.shared.u16 [%0], %1;" :: "r"(a), "h"((unsigned short)(pack_bf16(v, 0.f) & 0xffff)) : "memory"); }
__device__ __forceinline__ void spin_until(long long t0, long long due) { for (int it = 0; it < 100000 && clock64() - t0 < due; it++) {} }
#define PF_1 1
#define PF_2 3
#define W_EARLY 2
#define SKEW 1
#define PUB 2
#define SUB 0
#define PF_L2 2

__global__ void __cluster_dims__(2, 1, 1) __launch_bounds__(512, 1)
fused_kernel(const __grid_constant__ Params p, const __grid_constant__ Maps mp) {
  extern __shared__ __align__(1024) char smem_raw[];
  const int bid = __shfl_sync(0xffffffffu, (int)blockIdx.x, 0);
  const uint32_t sb = __shfl_sync(0xffffffffu, (uint32_t)__cvta_generic_to_shared(smem_raw), 0);
  const int lane = __shfl_sync(0xffffffffu, (int)threadIdx.x & 31, threadIdx.x & 31), w = __shfl_sync(0xffffffffu, (int)threadIdx.x >> 5, 0);
  const int tid = w * 32 + lane, g = lane >> 2, c = lane & 3;
  const bool regular = bid < 128;
  const int m = bid;
  const int rt = bid >> 3, jb = (bid >> 1) & 3, kh = bid & 1;
  const int f0 = 688 * kh + 176 * jb;

  if (!regular && w >= 8) return;

  uint2 xr[4];
  if (regular) {
    const uint32_t* xp = p.x + (128 * w + m) * 256 + 64 * c + 2 * g;
#pragma unroll
    for (int i = 0; i < 4; i++) xr[i] = ldg_nc2(xp + 16 * i);
  }
  const int grp = regular ? 16 * (bid & 7) + w : 120 + w;
  const uint32_t sect = ld_rlx(p.sync + SY_FL + grp * 8 + (lane & 7));
  uint32_t epoch;
  if (tid == 160) {
#pragma unroll
    for (int i = 0; i < NSLOT; i++) { mbar_init(sb + B_FULL + i * 8, 2); mbar_init(sb + B_EMPTY + i * 8, 8); }
    mbar_init(sb + B_W, 1); mbar_init(sb + B_XFREE, 1); mbar_init(sb + B_T, 1);
#pragma unroll
    for (int i = 0; i < 4; i++) mbar_init(sb + B_AE + i * 8, 4);
#pragma unroll
    for (int i = 0; i < 8; i++) mbar_init(sb + B_X + i * 8, 1);
#pragma unroll
    for (int i = 0; i < NSLOT; i++) sts1(sb + TOK + i * 4, 0);
    asm volatile("fence.mbarrier_init.release.cluster;" ::: "memory");
#pragma unroll
    for (int i = 0; i < 8; i++) mbar_expect(sb + B_X + i * 8, 2048);
    if (!regular) { mbar_expect(sb + B_T, 33280); bulk_load(sb + T_G, p.tab + 320, 33280, sb + B_T); }
    else if (W_EARLY == 2) {
      const int r = bid >> 3, p0 = 16 * (bid & 7), r2 = (16 - r) & 15, ca = (r * 257 + p0) & ~7, cb = (r2 * 257 + 241 - p0) & ~7;
      mbar_expect(sb + B_W, 24576);
      tma3d(sb + WST, &mp.wr, ca, 0, 0, sb + B_W);
      tma3d(sb + WST + 6144, &mp.wi, ca, 0, 0, sb + B_W);
      tma3d(sb + WST + 12288, &mp.wr, cb, 0, 0, sb + B_W);
      tma3d(sb + WST + 18432, &mp.wi, cb, 0, 0, sb + B_W);
    }
  }
  if (tid == 224 && regular) {
#pragma unroll
    for (int i = 0; i < 32; i++) mbar_init(sb + B_A + i * 8, 1);
    asm volatile("fence.mbarrier_init.release.cluster;" ::: "memory");
  }
  if (tid == 192 && regular) {
    tmap_prefetch(&mp.wr); tmap_prefetch(&mp.wi); tmap_prefetch(&mp.wg); tmap_prefetch(&mp.wu); tmap_prefetch(&mp.wd64); tmap_prefetch(&mp.wd16);
    if (bid < 65) l2_prefetch(p.tab + (10 + bid) * 32, 512);
  }

  if (regular) {
    float sn, cs;
    if (tid < 256) {
      const int r = tid >> 4, j = tid & 15;
      const int idx = ((r * (128 * j + m) + 1024) & 2047) - 1024;
      sincos_idx(idx, 6.283185307179586f / 2048.f, sn, cs);
      const uint32_t ao = ((r & 7) * 4 + ((j & 7) >> 1)) * 16 + ((r >> 3) + 2 * (j >> 3)) * 4 + (j & 1) * 2;
      sts_h(sb + T_AR + ao, cs); sts_h(sb + T_AI + ao, -sn);
      const int reg = 8 * (r >> 3) + 2 * (j >> 2) + ((r >> 2) & 1);
      const uint32_t bo = sb + T_BF + (reg >> 2) * 512 + ((j & 3) * 8 + (r & 3)) * 16 + (reg & 3) * 4;
      sts1(bo, pack_bf16(cs, sn)); sts1(bo + 64, pack_bf16(-sn, cs));
    } else {
      const int x = tid - 256, i = x >> 6, l = (x >> 1) & 31;
      const int idx = ((l >> 2) + 8 * (i >> 1)) * (4 * (l & 3) + 2 * (i & 1) + (x & 1));
      sincos_idx(((idx + 128) & 255) - 128, 6.283185307179586f / 256.f, sn, cs);
      sts2(sb + T_TW + x * 8, __float_as_uint(cs), __float_as_uint(-sn));
    }
    if (tid >= 384) {
      const int x = tid - 384, k1 = (x >> 4) + 8 * (x & 1), n1 = 4 * ((x >> 2) & 3) + (x & 2);
      float s1, c1;
      sincos_idx(((k1 * n1 + 8) & 15) - 8, 6.283185307179586f / 16.f, sn, cs);
      sincos_idx(((k1 * (n1 + 1) + 8) & 15) - 8, 6.283185307179586f / 16.f, s1, c1);
      sts1(sb + T_FR + x * 4, pack_bf16(cs, c1)); sts1(sb + T_FI + x * 4, pack_bf16(-sn, -s1));
    }
    TS(0);
    __syncthreads();
    asm volatile("barrier.cluster.arrive.relaxed.aligned;" ::: "memory");
    auto issue_w = [&]() {
      if (W_EARLY != 2 && lane == 0 && (w & 3) == 3) {
        const int r = bid >> 3, p0 = 16 * (bid & 7), r2 = (16 - r) & 15, q = w >> 2;
        if (q == 0) mbar_expect(sb + B_W, 24576);
        tma3d(sb + WST + q * 6144, (q & 1) ? &mp.wi : &mp.wr, ((q & 2) ? r2 * 257 + 241 - p0 : r * 257 + p0) & ~7, 0, 0, sb + B_W);
      }
      if (lane == 0 && w == 5) { mbar_expect(sb + B_T, 33280); bulk_load(sb + T_G, p.tab + 320, 33280, sb + B_T); }
    };
    if (W_EARLY == 1) issue_w();
    DConst dk;
    dk.fr = lds4(sb + T_FR + lane * 16); dk.fi = lds4(sb + T_FI + lane * 16);
    dk.nfi = xor4(dk.fi, 0x80008000u);
    const uint4 ia = make_uint4(dk.fi.x, dk.fi.z, dk.nfi.y, dk.nfi.w);
    const uint4 ib = make_uint4(dk.fr.x, dk.fr.z, dk.fr.y ^ 0x80008000u, dk.fr.w ^ 0x80008000u);
    const int padc = (c & 1) * 4 + (c >> 1) * 16, padr = ((3 - c) & 1) * 4 + ((3 - c) >> 1) * 16, pad4 = ((4 - c) & 1) * 4 + ((4 - c) >> 1) * 16;
    const uint32_t row = sb + EXA + w * 1200;
    const uint32_t aa = row + (64 * c + padc + 8 * (g & 1) + (g >> 1)) * 4;
    const uint32_t ab = row + (g ? (16 * (15 - 4 * c) + padr + 8 * (g & 1) + 4 + ((8 - g) >> 1)) : (16 * (16 - 4 * c) + padr + 4)) * 4;
    const uint32_t ab0 = g ? ab : (c ? row + (16 * (16 - 4 * c) + pad4 + 4) * 4 : row + 289 * 4);
    const uint32_t la = sb + EXA + (((lane >> 3) & 1) * 8 + (lane & 7)) * 1200 + (16 * w + ((w >> 2) & 1) * 4 + (w >> 3) * 16 + 4 * (lane >> 4)) * 4;
    char* dst = p.T + m * TP + (g * 8 + (w >> 1)) * 128 + (w & 1) * 64 + c * 16;
    uint32_t* flagp = p.sync + SY_FL + (w * 8 + (m & 7)) * 8;
    pin(sb + DUMMY, aa ^ ab ^ ab0 ^ la ^ (uint32_t)(size_t)dst ^ (uint32_t)(size_t)flagp ^ ib.z ^ ib.w ^ dk.nfi.x ^ dk.nfi.y ^ dk.nfi.z ^ dk.nfi.w);
    TS(6);
    uint32_t b[8];
#pragma unroll
    for (int f = 0; f < 2; f++) {
      b[f] = prmt(xr[2 * f].x, xr[2 * f + 1].x, 0x5410);     b[4 + f] = prmt(xr[2 * f].x, xr[2 * f + 1].x, 0x7632);
      b[2 + f] = prmt(xr[2 * f].y, xr[2 * f + 1].y, 0x5410); b[6 + f] = prmt(xr[2 * f].y, xr[2 * f + 1].y, 0x7632);
    }
    if (W_EARLY != 1) { pin(sb + DUMMY, b[0] ^ b[1]); issue_w(); }
    TS(2);
#pragma unroll
    for (int i = 0; i < 4; i++) dk.tw[i] = lds4(sb + T_TW + i * 512 + lane * 16);
    const uint4 ar = lds4(sb + T_AR + lane * 16), ai = lds4(sb + T_AI + lane * 16);
    const float rstd = ln_center(b);
    const uint32_t bre[2][2] = {{b[0], b[1]}, {b[2], b[3]}}, bim[2][2] = {{b[4], b[5]}, {b[6], b[7]}};
    float ore[2][4], oim[2][4];
    dstage(dk, dk.fr, dk.nfi, ia, ib, bre, bim, ore, oim);
#pragma unroll
    for (int i = 0; i < 4; i++) { ore[0][i] *= rstd; oim[0][i] *= rstd; ore[1][i] *= rstd; oim[1][i] *= rstd; }
    if (lane == 0) {
      sts1(row + 4 * 4, pack_bf16(ore[0][0] - oim[0][0], 0.f));
      sts1(row + 288 * 4, pack_bf16(ore[1][0], -oim[1][0]));
      ore[0][0] += oim[0][0]; oim[0][0] = 0.f;
    }
    sts1(aa, pack_bf16(ore[0][0], oim[0][0]));
    sts1(aa + 64, pack_bf16(ore[0][2], oim[0][2]));
    sts1(aa + 128, pack_bf16(ore[0][1], oim[0][1]));
    sts1(aa + 192, pack_bf16(ore[0][3], oim[0][3]));
    sts1(ab0, pack_bf16(ore[1][0], oim[1][0]));
    sts1(ab - 64, pack_bf16(ore[1][2], oim[1][2]));
    sts1(ab - 128, pack_bf16(ore[1][1], oim[1][1]));
    sts1(ab - 192, pack_bf16(ore[1][3], oim[1][3]));
    epoch = __shfl_sync(0xffffffffu, sect, 4);
    if (tid == 0) sts1(sb + EPO, epoch);
    TS(5);
    __syncthreads();
    {
      const uint4 b01 = ldsm4t(la), b23 = ldsm4t(la + 32);
      const uint2 bx = ldsm2t(sb + EXA + (lane & 15) * 1200 + 288 * 4);
      const uint32_t bb[4][2] = {{b01.x, b01.y}, {b01.z, b01.w}, {b23.x, b23.y}, {b23.z, b23.w}};
      uint32_t o[2][4];
#pragma unroll
      for (int t = 0; t < 4; t++) {
        float tr[4], ti[4];
        mma16z(tr, ar.x, ar.y, ar.z, ar.w, bb[t][0], bb[t][1]);
        mma16z(ti, ai.x, ai.y, ai.z, ai.w, bb[t][0], bb[t][1]);
        o[0][t] = pack_bf16(tr[0] - ti[1], tr[1] + ti[0]);
        o[1][t] = pack_bf16(tr[2] - ti[3], tr[3] + ti[2]);
      }
      {
        float tr[4], ti[4];
        mma16z(tr, ar.x, ar.y, ar.z, ar.w, bx.x, bx.y);
        mma16z(ti, ai.x, ai.y, ai.z, ai.w, bx.x, bx.y);
        const uint32_t e0 = pack_bf16(tr[0] - ti[1], tr[1] + ti[0]), e1 = pack_bf16(tr[2] - ti[3], tr[3] + ti[2]);
        const uint32_t f0_ = __shfl_down_sync(0xffffffffu, e0, 1), f1_ = __shfl_down_sync(0xffffffffu, e1, 1);
        if (w == 15 && c == 0) { char* de = p.T + m * TP + 16384 + g * 8; st_rlx2(de, tag1(e0), f0_); st_rlx2(de + 64, tag1(e1), f1_); }
      }
      TS(3);
      st_rlx4(dst, tag1(o[0][0]), tag0(o[0][1]), tag1(o[0][2]), tag0(o[0][3]));
      st_rlx4(dst + 64 * 128, tag1(o[1][0]), tag0(o[1][1]), tag1(o[1][2]), tag0(o[1][3]));
      __syncwarp();
      if (lane == 0) red_add(flagp, 1);
    }
    if (lane == 0 && (w & 1) == 0 && (w >> 2) < PF_1) issue_g1_half(mp, sb, w >> 2, f0, (w >> 1) & 1);
    if (PF_L2 == 1 && tid == 416) { l2_prefetch(p.wg + bid * 11008, 11008); l2_prefetch(p.wu + bid * 11008, 11008); l2_prefetch(p.wd + bid * 11008, 11008); }
    TS(7);
  } else {
    bar_sync(9, 256);
    epoch = __shfl_sync(0xffffffffu, sect, 4);
  }

  {
    const int h = regular ? w >> 3 : bid - 128, u = w & 7;
    const uint32_t want = (epoch + 1) * 16;
    const uint32_t* fp = p.sync + SY_FL + grp * 8;
    float al[4][2], be[4][2], ga[4][2];
    uint32_t m1[16], m2[16];
    const uint32_t tl = sb + T_G + lane * 16;
    mbar_wait(sb + B_T, 0);
#pragma unroll
    for (int i = 0; i < 4; i++) { const uint4 v = lds4(tl + (1 + u * 4 + i) * 512); m1[4 * i] = v.x; m1[4 * i + 1] = v.y; m1[4 * i + 2] = v.z; m1[4 * i + 3] = v.w; }
    const uint4 b8 = lds4(tl);
    if (!regular) {
#pragma unroll
      for (int i = 0; i < 4; i++) al[i][0] = al[i][1] = be[i][0] = be[i][1] = ga[i][0] = ga[i][1] = 0.f;
    } else {
      const int pl = 8 * h + g;
      const int r = bid >> 3, pp = 16 * (bid & 7) + pl, r2 = (16 - r) & 15;
      float sn, cs;
      __sincosf((float)pp * (6.283185307179586f / 512.f), &sn, &cs);
      if (pp == 0) { sn = -1.f; cs = 0.f; }
      const float sc = 9.5367431640625e-07f;
      sn *= sc; cs *= sc;
      const uint32_t wa = sb + WST + ((r & 7) + pl) * 2;
      const uint32_t wb = sb + WST + 12288 + (((r2 + 1) & 7) + 15 - pl) * 2;
      mbar_wait(sb + B_W, 0);
      if ((bid & 7) == 7 && w == 15) {
        uint32_t v[4];
#pragma unroll
        for (int i = 0; i < 4; i++) {
          const uint32_t a_ = sb + WST + ((r & 7) + 16) * 2 + ((g + 8 * (i >> 1)) * 8 + c + 4 * (i & 1)) * 48;
          v[i] = pack_bf16(lds_bf(a_), lds_bf(a_ + 6144));
        }
        st_rlx4(p.WX + r * 1024 + lane * 32, v[0], epoch + 1, v[1], epoch + 1);
        st_rlx4(p.WX + r * 1024 + lane * 32 + 16, v[2], epoch + 1, v[3], epoch + 1);
      }
#pragma unroll
      for (int z = 0; z < 2; z++)
#pragma unroll
        for (int t = 0; t < 2; t++) {
          const int q1 = u + 8 * z, q2 = c + 4 * t;
          const int k1 = r ? 15 - q1 : (16 - q1) & 15, k2 = (r || q1) ? 7 - q2 : (8 - q2) & 7;
          const float w1r = lds_bf(wa + (q1 * 8 + q2) * 48), w1i = lds_bf(wa + (q1 * 8 + q2) * 48 + 6144);
          const float w2r = lds_bf(wb + (k1 * 8 + k2) * 48), w2i = -lds_bf(wb + (k1 * 8 + k2) * 48 + 6144);
          const float sr = (w1r + w2r) * sc, si = (w1i + w2i) * sc, dr = w1r - w2r, di = w1i - w2i;
          al[2 * z + t][0] = fmaf(-sn, dr, sr); al[2 * z + t][1] = fmaf(-sn, di, si);
          ga[2 * z + t][0] = fmaf(sn, dr, sr);  ga[2 * z + t][1] = fmaf(sn, di, si);
          be[2 * z + t][0] = -cs * di;          be[2 * z + t][1] = cs * dr;
        }
    }
    uint32_t px = 0;
#pragma unroll
    for (int i = 0; i < 4; i++)
      px ^= __float_as_uint(al[i][0]) ^ __float_as_uint(al[i][1]) ^ __float_as_uint(ga[i][0]) ^ __float_as_uint(ga[i][1]) ^ __float_as_uint(be[i][0]) ^ __float_as_uint(be[i][1]);
    char* tp = p.T + (8 * c + u) * TP + (regular ? bid : 128) * 128 + (8 * h + g) * 8;
    const uint32_t e1 = sb + EXB + (h * 1024 + c * 64 + (u >> 2) * 32 + (g >> 2) * 16 + ((c + u) & 3) * 4 + (g & 3)) * 8;
    const uint32_t e2 = sb + EXB + (h * 1024 + u * 64 + (g >> 2) * 16 + ((c + u) & 3) * 4 + (g & 3)) * 8;
    pin(sb + DUMMY, px ^ e1 ^ e2 ^ (uint32_t)(size_t)tp ^ m1[0] ^ m1[15] ^ b8.x);
    TS(8);
    {
      int it = 0;
      while ((int)(ld_rlx(fp) - want) < 0 && ++it < SPIN_LIMIT) {}
    }
    TS(9);
    uint2 a[4];
    {
      int it = 0;
      do {
#pragma unroll
        for (int i = 0; i < 4; i++) a[i] = ld_rlx2(tp + i * 32 * TP);
      } while (__any_sync(0xffffffffu, ~and4(a) & 1u) && ++it < SPIN_LIMIT);
    }
    TS(4);
    if (PF_L2 == 2 && regular && tid == 416) { l2_prefetch(p.wg + bid * 11008, 11008); l2_prefetch(p.wu + bid * 11008, 11008); l2_prefetch(p.wd + bid * 11008, 11008); }
    float o[4][4];
    r16(o, a, m1);
#pragma unroll
    for (int t = 0; t < 4; t++) sts2(e1 + t * 2048, pack_bf16(o[t][0], o[t][1]), pack_bf16(o[t][2], o[t][3]));
    TS(10);
    if (!regular) {
      const char* wx = p.WX + (8 * h + g) * 1024 + (u * 4 + c) * 32;
      uint32_t v[4], e[4]; int it = 0;
      do { ld_rlx4(wx, v[0], e[0], v[1], e[1]); ld_rlx4(wx + 16, v[2], e[2], v[3], e[3]); }
      while (__any_sync(0xffffffffu, (e[0] != epoch + 1) | (e[1] != epoch + 1) | (e[2] != epoch + 1) | (e[3] != epoch + 1)) && ++it < SPIN_LIMIT);
#pragma unroll
      for (int i = 0; i < 4; i++) { ga[i][0] = bf_lo(v[i]) * 1.9073486328125e-06f; ga[i][1] = bf_hi(v[i]) * 1.9073486328125e-06f; }
    }
#pragma unroll
    for (int i = 0; i < 4; i++) { const uint4 v = lds4(tl + (33 + u * 4 + i) * 512); m2[4 * i] = v.x; m2[4 * i + 1] = v.y; m2[4 * i + 2] = v.z; m2[4 * i + 3] = v.w; }
    bar_sync(1 + h, 256);
#pragma unroll
    for (int z = 0; z < 2; z++) {
      const uint2 x0 = lds2(e2 + z * 4096), x1 = lds2(e2 + z * 4096 + 256);
      float y[2][4];
      mma16z(y[0], x0.x, x0.y, x1.x, x1.y, b8.x, b8.y);
      mma16z(y[1], x0.x, x0.y, x1.x, x1.y, b8.z, b8.w);
      uint32_t ga_[2], gb_[2];
#pragma unroll
      for (int t = 0; t < 2; t++) {
        const float arr = y[t][0], aii = y[t][1], brr = y[t][2], bii = y[t][3];
        const float* A = al[2 * z + t]; const float* B = be[2 * z + t]; const float* Gm = ga[2 * z + t];
        const float pr = fmaf(A[0], arr, fmaf(-A[1], aii, fmaf(B[0], brr, -B[1] * bii)));
        const float pi = fmaf(-A[0], aii, fmaf(-A[1], arr, fmaf(-B[0], bii, -B[1] * brr)));
        const float cr = fmaf(Gm[0], brr, fmaf(-Gm[1], bii, fmaf(-B[0], arr, B[1] * aii)));
        const float ci = fmaf(-Gm[0], bii, fmaf(-Gm[1], brr, fmaf(B[0], aii, B[1] * arr)));
        ga_[t] = pack_bf16(pr, pi); gb_[t] = pack_bf16(cr, ci);
      }
      mma16z(y[0], ga_[0], gb_[0], ga_[1], gb_[1], b8.x, b8.y);
      mma16z(y[1], ga_[0], gb_[0], ga_[1], gb_[1], b8.z, b8.w);
#pragma unroll
      for (int t = 0; t < 2; t++) sts2(e2 + z * 4096 + t * 256, pack_bf16(y[t][0], y[t][1]), pack_bf16(y[t][2], y[t][3]));
    }
    bar_sync(1 + h, 256);
#pragma unroll
    for (int i = 0; i < 4; i++) a[i] = lds2(e1 + i * 2048);
    r16(o, a, m2);
    TS(1);
#pragma unroll
    for (int t = 0; t < 4; t++) st_rlx2(tp + t * 32 * TP, tag0(pack_bf16(o[t][0], o[t][1])), tag0(pack_bf16(o[t][2], o[t][3])));
    if (regular && lane == 0 && (w & 1) == 0 && PF_1 + (w >> 2) < PF_2) issue_g1_half(mp, sb, PF_1 + (w >> 2), f0, (w >> 1) & 1);
    if (PF_L2 == 3 && regular && tid == 416) { l2_prefetch(p.wg + bid * 11008, 11008); l2_prefetch(p.wu + bid * 11008, 11008); l2_prefetch(p.wd + bid * 11008, 11008); }
    TS(11);
  }
  if (!regular) { TS_FLUSH(); return; }

  {
    __syncwarp();
    const char* tp = p.T + m * TP + (c * 8 + (w >> 1)) * 128 + (w & 1) * 64 + g * 8;
    uint32_t bf[16];
#pragma unroll
    for (int i = 0; i < 4; i++) { const uint4 v = lds4(sb + T_BF + i * 512 + lane * 16); bf[4 * i] = v.x; bf[4 * i + 1] = v.y; bf[4 * i + 2] = v.z; bf[4 * i + 3] = v.w; }
    const char* tx = p.T + m * TP + 16384 + c * 8;
    uint2 a[4], ae[4];
#pragma unroll
    for (int i = 0; i < 4; i++) { a[i] = ld_rlx2(tp + i * 4096); ae[i] = make_uint2(0, 0); }
    if (w == 15) {
#pragma unroll
      for (int i = 0; i < 4; i++) ae[i] = ld_rlx2(tx + i * 32);
    }
    DConst dk;
    dk.fr = lds4(sb + T_FR + lane * 16); dk.fi = lds4(sb + T_FI + lane * 16);
#pragma unroll
    for (int i = 0; i < 4; i++) dk.tw[i] = lds4(sb + T_TW + i * 512 + lane * 16);
    uint32_t xw[8];
    {
      const uint32_t* xp = p.x + (128 * w + m) * 256 + g + 32 * c;
#pragma unroll
      for (int i = 0; i < 8; i++) xw[i] = ldg_nc1(xp + 128 * (i >> 2) + 8 * ((i >> 1) & 1) + 16 * (i & 1));
    }
    const int pp = 8 * w + g, kb = 256 - pp;
    const uint32_t aa = sb + EXA + (c * 264 + (pp ^ ((pp >> 3) & 24))) * 4;
    const uint32_t ab = sb + EXA + (c * 264 + (kb ^ ((kb >> 3) & 24))) * 4;
    pin(sb + DUMMY, bf[0] ^ bf[15] ^ aa ^ ab ^ dk.fr.x ^ dk.tw[3].x);
    TS(12);
    {
      int it = 0;
      while (__any_sync(0xffffffffu, (or4(a) | or4(ae)) & 1u) && ++it < SPIN_LIMIT) {
#pragma unroll
        for (int i = 0; i < 4; i++) a[i] = ld_rlx2(tp + i * 4096);
        if (w == 15) {
#pragma unroll
          for (int i = 0; i < 4; i++) ae[i] = ld_rlx2(tx + i * 32);
        }
      }
    }
    TS(13);
    float o[4][4];
    r16(o, a, bf);
    if (w == 0) {
#pragma unroll
      for (int t = 0; t < 4; t++) if (g == 0) { const float P = o[t][0], Q = o[t][2]; o[t][0] = 0.5f * (P + Q); o[t][1] = 0.5f * (Q - P); }
    }
#pragma unroll
    for (int t = 0; t < 4; t++) {
      sts1(aa + t * 4224, pack_bf16(o[t][0], o[t][1]));
      sts1(ab + t * 4224, pack_bf16(o[t][2], o[t][3]));
    }
    if (w == 15) {
      r16(o, ae, bf);
      if (g == 0) {
#pragma unroll
        for (int t = 0; t < 4; t++) sts1(sb + EXA + (c * 264 + 144) * 4 + t * 4224, pack_bf16(o[t][2], o[t][3]));
      }
    }
    dk.nfi = xor4(dk.fi, 0x80008000u);
    const uint32_t cm = c >= 2 ? 0x80008000u : 0u;
    const uint4 fr2 = xor4(dk.fr, cm), nfi2 = xor4(dk.nfi, cm), ia = swap4(dk.nfi), ib = swap4(xor4(dk.fr, 0x80008000u));
    const uint32_t la0 = sb + EXA + (w * 264 + ((64 * c + 2 * g) ^ (8 * c))) * 4, la1 = sb + EXA + (w * 264 + ((64 * c + 2 * g) ^ (8 * c) ^ 16)) * 4;
    const uint32_t so = sb + w * 1024 + c * 128 + ((((g >> 2) ^ (2 * c) ^ w) & 7) << 4) + (g & 3) * 4;
    pin(sb + DUMMY, fr2.x ^ fr2.w ^ nfi2.x ^ nfi2.w ^ ib.x ^ ib.w ^ la0 ^ la1 ^ so);
    TS(14);
    __syncthreads();
    uint32_t bre[2][2], bim[2][2];
    {
      const uint2 d0 = lds2(la0), d1 = lds2(la1), d2 = lds2(la0 + 128), d3 = lds2(la1 + 128);
      bre[0][0] = prmt(d0.x, d1.x, 0x5410); bim[0][0] = prmt(d0.x, d1.x, 0x7632); bre[1][0] = prmt(d0.y, d1.y, 0x5410); bim[1][0] = prmt(d0.y, d1.y, 0x7632);
      bre[0][1] = prmt(d2.x, d3.x, 0x5410); bim[0][1] = prmt(d2.x, d3.x, 0x7632); bre[1][1] = prmt(d2.y, d3.y, 0x5410); bim[1][1] = prmt(d2.y, d3.y, 0x7632);
    }
    float ore[2][4], oim[2][4];
    dstage(dk, fr2, nfi2, ia, ib, bre, bim, ore, oim);
    uint32_t hw[8];
#pragma unroll
    for (int i = 0; i < 8; i++) {
      hw[i] = hadd2b(xw[i], pack_bf16(ore[i >> 2][i & 3], oim[i >> 2][i & 3]));
      sts1(((so ^ (((i >> 1) & 1) << 5) ^ ((i & 1) << 6)) + (i >> 2) * 512) + WST, hw[i]);
    }
    TS(15);
    const float rstd = ln_center(hw);
    {
      const uint32_t rh = pack_bf16(rstd, rstd);
      const float rl_ = rstd - bf_lo(rh);
      const uint32_t rl = pack_bf16(rl_, rl_);
#pragma unroll
      for (int i = 0; i < 8; i++) sts1(((so ^ (((i >> 1) & 1) << 5) ^ ((i & 1) << 6)) + (i >> 2) * 512) + EXB, hfma2b(hw[i], rh, hmul2b(hw[i], rl)));
    }
    const int srow = ((lane >> 3) & 1) * 8 + (lane & 7), sch = 4 * w + (lane >> 4);
    const uint32_t sl0 = sb + srow * 1024 + ((sch ^ (((sch >> 3) & 3) << 1) ^ (srow & 7)) << 4);
    char* lnp = p.T + m * TP + (2 * w * 32 + lane) * 16;
    char* hrp = p.HR + m * 16384 + (2 * w * 32 + lane) * 16;
    TS(16);
    __syncthreads();
    {
      const uint4 l0 = ldsm4(sl0 + EXB), l1 = ldsm4((sl0 ^ 32) + EXB), h0 = ldsm4(sl0 + WST), h1 = ldsm4((sl0 ^ 32) + WST);
      st_rlx4(lnp, tag0(l0.x), tag1(l0.y), tag0(l0.z), tag1(l0.w));
      st_rlx4(lnp + 512, tag0(l1.x), tag1(l1.y), tag0(l1.z), tag1(l1.w));
      TS(17);
      stg4(hrp, h0.x, h0.y, h0.z, h0.w);
      stg4(hrp + 512, h1.x, h1.y, h1.z, h1.w);
    }
    __syncthreads();
  }

  if (w >= 8) {
    asm volatile("setmaxnreg.dec.sync.aligned.u32 32;");
    asm volatile("barrier.cluster.wait.aligned;" ::: "memory");
    const uint32_t epoch = lds1(sb + EPO);
    if (w < 12) {
      const int pr = w - 8, src = 8 * rt + 2 * pr + kh;
      const int n0 = 128 * jb + 64 * kh, n1 = 128 * jb + 64 * (1 - kh);
#pragma unroll 1
      for (int t = 0; t < 3; t++) {
        const int s = 12 + 4 * t + pr, slot = s % NSLOT, nk = t < 2 ? 4 : (pr < 3 ? 3 : 2), fr = 688 * kh + 176 * pr + 64 * t;
        const uint32_t bar = sb + B_FULL + slot * 8, dst = sb + slot * SLOT;
        const uint32_t* hf = p.sync + SY_H + (src * 2 + (lane & 1)) * 8;
        if (t < 2) { wait_ge_sleep(hf, epoch * 3 + t + 1); __syncwarp(); }
        if (lane == 0) {
          acquire_slot(sb, s);
          mbar_expect(bar, nk * 4096);
          if (t < 2) {
            tma2d(dst + 16384, &mp.wd64, n0, fr, bar);
            tma2d(dst + 16384 + 8192, &mp.wd64, n1, fr, bar);
          } else {
            for (int k = 0; k < nk; k++) {
              tma2d(dst + 16384 + k * 2048, &mp.wd16, n0, fr + 16 * k, bar);
              tma2d(dst + 16384 + 8192 + k * 2048, &mp.wd16, n1, fr + 16 * k, bar);
            }
          }
          TS(20 + 2 * t);
        }
        __syncwarp();
        if (t == 2) { wait_ge_rlx(hf, epoch * 3 + t + 1); __syncwarp(); }
        if (lane == 0) {
          const char* hs = p.H + (src * 3 + t) * 16384;
          mbar_expect(bar, nk * 4096);
          if (t < 2) bulk_load(dst, hs, 16384, bar);
          else
          { bulk_load(dst, hs, nk * 2048, bar); bulk_load(dst + 8192, hs + 8192, nk * 2048, bar); }
          TS(21 + 2 * t);
        }
        __syncwarp();
      }
    } else if (w == 12) {
      if (lane == 0) {
#pragma unroll 1
        for (int s = PF_2; s < 3; s++) issue_g1(mp, sb, s, f0);
#pragma unroll 1
        for (int s = 3; s < 7; s++) { mbar_wait(sb + B_AE + (s - 3) * 8, 0); issue_g1(mp, sb, s, f0); TS(14 + s); }
#pragma unroll 1
        for (int s = 7; s < 12; s++) { acquire_slot(sb, s); issue_g1(mp, sb, s, f0); TS(14 + s); }
        int it = 0; uint32_t v;
        while (true) {
          asm volatile("ld.volatile.shared.u32 %0, [%1];" : "=r"(v) : "r"(sb + TOK + XSLOT * 4) : "memory");
          if (v == 17 / NSLOT || ++it > SPIN_LIMIT) break;
          __nanosleep(500);
        }
        mbar_wait(sb + B_EMPTY + XSLOT * 8, (17 / NSLOT) & 1);
        uint32_t rem;
        asm volatile("mapa.shared::cluster.u32 %0, %1, %2;" : "=r"(rem) : "r"(sb + B_XFREE), "r"(kh ^ 1));
        asm volatile("mbarrier.arrive.release.cluster.shared::cluster.b64 _, [%0];" :: "r"(rem) : "memory");
      }
    } else if (w == 15) {
      if (bid < 8 && lane < 16) st_rlx(p.sync + SY_FL + (16 * bid + lane) * 8 + 4, epoch + 1);
      {
        const char* hp_ = p.HR + bid * 16384 + lane * 128;
        pin(sb + DUMMY, ld_rlx(hp_) ^ ld_rlx(hp_ + 4096) ^ ld_rlx(hp_ + 8192) ^ ld_rlx(hp_ + 12288));
        __syncwarp();
        if (lane == 0) red_add(p.sync + SY_HR + bid * 8, 1);
      }
    } else {
      const int wg = w - 13;
#pragma unroll 1
      for (int t = 0; t < 3; t++) {
        bar_sync(4 + wg, 160);
        TS(24 + t);
        const char* hdst = p.H + (bid * 3 + t) * 16384 + wg * 8192 + lane * 128;
        pin(sb + DUMMY, ld_rlx(hdst) ^ ((t < 2 || lane < 16) ? ld_rlx(hdst + 4096) : 0u));
        __syncwarp();
        if (lane == 0) { red_add(p.sync + SY_H + (bid * 2 + wg) * 8, 1); TS(21 + t); }
        __syncwarp();
      }
    }
  } else {
    asm volatile("setmaxnreg.inc.sync.aligned.u32 224;");
    TS(20);
    const int wg = w >> 2, wq = w & 3, mA = 8 * rt + w;
    const char* ap = p.T + mA * TP;
    const uint32_t ast = sb + AST + wg * 65536 + wq * 4096, abar = sb + B_A + w * 32;
    {
      int it = 0;
      while (__any_sync(0xffffffffu, ~ld_rlx2(ap + lane * 512).y & 1u) && ++it < SPIN_LIMIT) {}
    }
    TS(21);
    if (wg == 1) bar_sync(7, 256);
    if (lane == 0) {
#pragma unroll
      for (int q = 0; q < 4; q++) { mbar_expect(abar + q * 8, 4096); bulk_load(ast + q * 16384, ap + q * 4096, 4096, abar + q * 8); }
    }
    __syncwarp();
    if (wg == 0) bar_arrive(7, 256);
    TS(22);
    uint32_t A[128];
    auto load_a = [&](int q) {
#pragma unroll
      for (int j = 0; j < 8; j++) {
        const uint4 v = lds4(ast + q * 16384 + j * 512 + lane * 16);
        A[32 * q + 4 * j] = v.x; A[32 * q + 4 * j + 1] = v.y; A[32 * q + 4 * j + 2] = v.z; A[32 * q + 4 * j + 3] = v.w;
      }
    };
    auto check_a = [&](int q) {
      int it = 0;
      while (true) {
        uint32_t ok = 1;
#pragma unroll
        for (int j = 0; j < 16; j++) ok &= A[32 * q + 2 * j + 1];
        if (__all_sync(0xffffffffu, ok & 1u) || ++it > SPIN_LIMIT) break;
        if (lane == 0) { mbar_expect(abar + q * 8, 4096); bulk_load(ast + q * 16384, ap + q * 4096, 4096, abar + q * 8); }
        __syncwarp();
        mbar_wait(abar + q * 8, it & 1);
        load_a(q);
      }
      if ((q & 1) && lane == 0) mbar_arrive(sb + B_AE + (2 * wg + (q >> 1)) * 8);
    };
    float acc[64];
    char* hp = p.H + bid * 3 * 16384 + wg * 8192 + wq * 256 + lane * 4;
#pragma unroll
    for (int t = 0; t < 2; t++) {
#pragma unroll
      for (int kq = 0; kq < 4; kq++) {
        const int s = 4 * t + kq, slot = s % NSLOT;
        if (t == 0 && kq == 0) {
          mbar_wait(abar, 0);
          load_a(0);
          check_a(0);
          if (wg == 1) bar_sync(8, 256);
          TS(30);
        }
        mbar_wait(sb + B_FULL + slot * 8, (s / NSLOT) & 1);
        WG_FENCE();
#pragma unroll
        for (int ks = 0; ks < 8; ks++) {
          const int ai = (8 * kq + ks) * 4;
          wgmma_rs_n128(acc, A[ai], A[ai + 1], A[ai + 2], A[ai + 3], mkdesc(sb + slot * SLOT + ks * 2048, 16384, 1024, 1), (kq | ks) != 0);
          if (t == 0 && kq < 3 && ks == 3) { mbar_wait(abar + (kq + 1) * 8, 0); load_a(kq + 1); }
        }
        WG_COMMIT();
        if (t == 0 && kq == SKEW && wg == 0) bar_arrive(8, 256);
        if (t == 0 && kq < 3) check_a(kq + 1);
        if (kq > 0) { WG_WAIT(1); if (lane == 0) mbar_arrive(sb + B_EMPTY + ((s - 1) % NSLOT) * 8); }
      }
      WG_WAIT(0);
      if (lane == 0) mbar_arrive(sb + B_EMPTY + ((4 * t + 3) % NSLOT) * 8);
      TS(23 + t);
#pragma unroll
      for (int i = 0; i < 32; i += 2)
        st_rlx(hp + t * 16384 + (i >> 2) * 1024 + (i & 2) * 64, pack_bf16(gelu2_mul(acc[i], acc[32 + i]), gelu2_mul(acc[i + 1], acc[33 + i])));
      bar_arrive(4 + wg, 160);
    }
    {
      float ag[24], au[24];
#pragma unroll
      for (int i = 0; i < 24; i++) { ag[i] = 0.f; au[i] = 0.f; }
#pragma unroll
      for (int kq = 0; kq < 4; kq++) {
        const int s = 8 + kq, slot = s % NSLOT;
        mbar_wait(sb + B_FULL + slot * 8, (s / NSLOT) & 1);
        WG_FENCE();
#pragma unroll
        for (int ks = 0; ks < 8; ks++) {
          const int ai = (8 * kq + ks) * 4;
          const uint64_t d = mkdesc(sb + slot * SLOT + ks * 2048, 16384, 1024, 1);
          wgmma_rs_n48(ag, A[ai], A[ai + 1], A[ai + 2], A[ai + 3], d, (kq | ks) != 0);
          wgmma_rs_n48(au, A[ai], A[ai + 1], A[ai + 2], A[ai + 3], d + (16384 >> 4), (kq | ks) != 0);
        }
        WG_COMMIT();
        if (kq > 0) { WG_WAIT(1); if (lane == 0) mbar_arrive(sb + B_EMPTY + ((s - 1) % NSLOT) * 8); }
      }
      WG_WAIT(0);
      if (lane == 0) mbar_arrive(sb + B_EMPTY + (11 % NSLOT) * 8);
      TS(25);
#pragma unroll
      for (int i = 0; i < 24; i += 2)
        st_rlx(hp + 2 * 16384 + (i >> 2) * 1024 + (i & 2) * 64, pack_bf16(gelu2_mul(ag[i], au[i]), gelu2_mul(ag[i + 1], au[i + 1])));
      bar_arrive(4 + wg, 160);
    }
    TS(26);
    uint4 hr[4];
#pragma unroll
    for (int sg = 0; sg < 12; sg++) {
      const int s = 12 + sg, slot = s % NSLOT, nk = sg < 8 ? 4 : (sg < 11 ? 3 : 2);
      mbar_wait(sb + B_FULL + slot * 8, (s / NSLOT) & 1);
      if (sg == 0) TS(18);
      if (sg == 8) TS(19);
      WG_FENCE();
#pragma unroll
      for (int ks = 0; ks < nk; ks++) {
        const uint64_t da = mkdesc(sb + slot * SLOT + wg * 8192 + ks * 2048, 1024, 128, 0);
        const uint64_t db = mkdesc(sb + slot * SLOT + 16384 + ks * 2048, 8192, 1024, 1);
        wgmma_ss_n128(acc, da, db, (sg | ks) != 0);
      }
      WG_COMMIT();
      if (sg == 1) {
        if (lane == 0) wait_ge_rlx(p.sync + SY_HR + mA * 8, lds1(sb + EPO) + 1);
        __syncwarp();
        const char* rp = p.HR + mA * 16384 + ((8 * jb + 4 * kh) * 32 + lane) * 16;
#pragma unroll
        for (int k = 0; k < 4; k++) ld_rlx4(rp + k * 512, hr[k].x, hr[k].y, hr[k].z, hr[k].w);
        asm volatile("barrier.cluster.wait.aligned;" ::: "memory");
      }
      if (sg > 0) { WG_WAIT(1); if (s - 1 <= 17 && lane == 0) mbar_arrive(sb + B_EMPTY + ((s - 1) % NSLOT) * 8); }
    }
    WG_WAIT(0);
    TS(27);
    {
      const uint32_t xb = sb + XSLOT * SLOT + w * 2048;
      uint32_t rdst, rbar;
      asm volatile("mapa.shared::cluster.u32 %0, %1, %2;" : "=r"(rdst) : "r"(xb + lane * 16), "r"(kh ^ 1));
      asm volatile("mapa.shared::cluster.u32 %0, %1, %2;" : "=r"(rbar) : "r"(sb + B_X + w * 8), "r"(kh ^ 1));
      mbar_wait_cluster(sb + B_XFREE, 0);
#pragma unroll
      for (int q = 0; q < 4; q++)
        asm volatile("st.async.weak.shared::cluster.mbarrier::complete_tx::bytes.v4.b32 [%0], {%1,%2,%3,%4}, [%5];"
                     :: "r"(rdst + q * 512), "r"(pack_bf16(acc[32 + 8 * q], acc[33 + 8 * q])), "r"(pack_bf16(acc[34 + 8 * q], acc[35 + 8 * q])),
                        "r"(pack_bf16(acc[36 + 8 * q], acc[37 + 8 * q])), "r"(pack_bf16(acc[38 + 8 * q], acc[39 + 8 * q])), "r"(rbar) : "memory");
      mbar_wait_cluster(sb + B_X + w * 8, 0);
      TS(28);
      uint32_t ow[8][2];
#pragma unroll
      for (int q = 0; q < 4; q++) {
        const uint4 pv = lds4(xb + q * 512 + lane * 16);
        ow[2 * q][0] = hadd2b(hr[q].x, pack_bf16(0.5f * (acc[8 * q] + bf_lo(pv.x)), 0.5f * (acc[8 * q + 1] + bf_hi(pv.x))));
        ow[2 * q][1] = hadd2b(hr[q].y, pack_bf16(0.5f * (acc[8 * q + 2] + bf_lo(pv.y)), 0.5f * (acc[8 * q + 3] + bf_hi(pv.y))));
        ow[2 * q + 1][0] = hadd2b(hr[q].z, pack_bf16(0.5f * (acc[8 * q + 4] + bf_lo(pv.z)), 0.5f * (acc[8 * q + 5] + bf_hi(pv.z))));
        ow[2 * q + 1][1] = hadd2b(hr[q].w, pack_bf16(0.5f * (acc[8 * q + 6] + bf_lo(pv.w)), 0.5f * (acc[8 * q + 7] + bf_hi(pv.w))));
      }
      __syncwarp();
      const int srow = ((lane >> 3) & 1) * 8 + (lane & 7);
#pragma unroll
      for (int q = 0; q < 8; q += 2)
        stsm4(xb + srow * 128 + (((q + (lane >> 4)) ^ (srow & 7)) << 4), ow[q][0], ow[q][1], ow[q + 1][0], ow[q + 1][1]);
      __syncwarp();
#pragma unroll
      for (int q = 0; q < 4; q++) {
        const int row = 4 * q + (lane >> 3), ch = lane & 7;
        const uint4 ov = lds4(xb + row * 128 + ((ch ^ (row & 7)) << 4));
        stg4(p.out + (128 * row + mA) * 256 + 64 * jb + 32 * kh + ch * 4, ov.x, ov.y, ov.z, ov.w);
      }
    }
    TS(29);
  }
  TS_FLUSH();
}

typedef CUresult (*EncodeFn)(CUtensorMap*, CUtensorMapDataType, cuuint32_t, void*, const cuuint64_t*, const cuuint64_t*, const cuuint32_t*,
                             const cuuint32_t*, CUtensorMapInterleave, CUtensorMapSwizzle, CUtensorMapL2promotion, CUtensorMapFloatOOBfill);

void make_map(EncodeFn fn, CUtensorMap* m, const void* base, int rank, const cuuint64_t* dims, const cuuint64_t* strides, const cuuint32_t* box,
              CUtensorMapSwizzle swz, CUtensorMapL2promotion promo) {
  const cuuint32_t es[3] = {1, 1, 1};
  fn(m, CU_TENSOR_MAP_DATA_TYPE_BFLOAT16, rank, const_cast<void*>(base), dims, strides, box, es, CU_TENSOR_MAP_INTERLEAVE_NONE, swz, promo,
     CU_TENSOR_MAP_FLOAT_OOB_FILL_NONE);
}

}

extern "C" void kernel_launch(void* const* d_in, const int* in_sizes, int n_in, void* d_out, int out_size) {
  static bool init = false;
  static EncodeFn encode = nullptr;
  static Params base;
  if (!init) {
    init = true;
    void* fn = nullptr;
    cudaDriverEntryPointQueryResult qr;
    cudaGetDriverEntryPoint("cuTensorMapEncodeTiled", &fn, cudaEnableDefault, &qr);
    encode = (EncodeFn)fn;
    cudaFuncSetAttribute(fused_kernel, cudaFuncAttributeMaxDynamicSharedMemorySize, SMEM_BYTES);
    void* a;
    cudaGetSymbolAddress(&a, g_T); base.T = (char*)a;
    cudaGetSymbolAddress(&a, g_HR); base.HR = (char*)a;
    cudaGetSymbolAddress(&a, g_H); base.H = (char*)a;
    cudaGetSymbolAddress(&a, g_WX); base.WX = (char*)a;
    cudaGetSymbolAddress(&a, g_sync); base.sync = (uint32_t*)a;
    cudaGetSymbolAddress(&a, g_tab); base.tab = (const uint4*)a;
    base.dbg = nullptr;
  }
  Params p = base;
  p.x = (const uint32_t*)d_in[0];
  p.out = (uint32_t*)d_out;
  p.wr = (const unsigned short*)d_in[1]; p.wi = (const unsigned short*)d_in[2];
  p.wg = (const char*)d_in[4]; p.wu = (const char*)d_in[5]; p.wd = (const char*)d_in[6];
  Maps mp;
  {
    const cuuint64_t dg[2] = {1376, 512}, sg[1] = {2752};
    const cuuint32_t bg[2] = {64, 128};
    make_map(encode, &mp.wg, d_in[4], 2, dg, sg, bg, CU_TENSOR_MAP_SWIZZLE_128B, CU_TENSOR_MAP_L2_PROMOTION_L2_128B);
    make_map(encode, &mp.wu, d_in[5], 2, dg, sg, bg, CU_TENSOR_MAP_SWIZZLE_128B, CU_TENSOR_MAP_L2_PROMOTION_L2_128B);
    const cuuint64_t dd[2] = {512, 1376}, sd[1] = {1024};
    const cuuint32_t b64[2] = {64, 64}, b16[2] = {64, 16};
    make_map(encode, &mp.wd64, d_in[6], 2, dd, sd, b64, CU_TENSOR_MAP_SWIZZLE_128B, CU_TENSOR_MAP_L2_PROMOTION_L2_128B);
    make_map(encode, &mp.wd16, d_in[6], 2, dd, sd, b16, CU_TENSOR_MAP_SWIZZLE_128B, CU_TENSOR_MAP_L2_PROMOTION_L2_128B);
    const cuuint64_t dw[3] = {4112, 8, 16}, sw[2] = {131584, 8224};
    const cuuint32_t bw[3] = {24, 8, 16};
    make_map(encode, &mp.wr, d_in[1], 3, dw, sw, bw, CU_TENSOR_MAP_SWIZZLE_NONE, CU_TENSOR_MAP_L2_PROMOTION_NONE);
    make_map(encode, &mp.wi, d_in[2], 3, dw, sw, bw, CU_TENSOR_MAP_SWIZZLE_NONE, CU_TENSOR_MAP_L2_PROMOTION_NONE);
  }
  fused_kernel<<<130, 512, SMEM_BYTES, cudaStreamPerThread>>>(p, mp);
}
```
